```python
import torch

def _softmax(x, axis=-1):
    return torch.softmax(x, dim=axis)
def _gelu(x):
    return torch.nn.functional.gelu(x, approximate="tanh")
def _silu(x):
    return torch.nn.functional.silu(x)
def _sigmoid(x):
    return torch.sigmoid(x)
def _layernorm(x, axis=-1, eps=1e-5):
    m = x.mean(dim=axis, keepdim=True)
    v = x.var(dim=axis, keepdim=True, unbiased=False)
    return (x - m) / torch.sqrt(v + eps)
def _scatter_add(tgt, idx, src, axis=0):
    return tgt.clone().index_add_(axis, idx, src)
def _segment_sum(src, seg, n):
    out = torch.zeros((n,) + src.shape[1:], dtype=src.dtype)
    return out.index_add_(0, seg, src)
def _pad(x, pw):
    flat = tuple(v for pair in reversed(pw) for v in pair)
    return torch.nn.functional.pad(x, flat)

kernel_name = 'standalone__gqa_softmax__near_ridge'

def setup_inputs():

    _w = (lambda a: (lambda t: t.to(torch.bfloat16) if t.is_floating_point() else t)(torch.as_tensor(a)))
    B, Hq, Hkv, Sq, Sk, D = 8, 16, 8, 256, 512, 256
    return {
        "q": _w((lambda *s: torch.randn(*s, dtype=torch.bfloat16) * 0.8)(B, Hq, Sq, D)),
        "k": _w((lambda *s: torch.randn(*s, dtype=torch.bfloat16) * 0.8)(B, Hkv, Sk, D)),
        "v": _w((lambda *s: torch.randn(*s, dtype=torch.bfloat16) * 0.05)(B, Hkv, Sk, D)),
    }

def reference(q, k, v):
    B, Hq, Sq, D = q.shape
    Hkv = k.shape[1]
    rep = Hq // Hkv
    k = (lambda x, n, axis: torch.repeat_interleave(x, n, dim=axis))(k, rep, axis=1)
    v = (lambda x, n, axis: torch.repeat_interleave(x, n, dim=axis))(v, rep, axis=1)
    scale = D ** -0.5
    scores = torch.einsum("bhqd,bhkd->bhqk", q, k) * scale
    p = _softmax(scores, axis=-1)
    return torch.einsum("bhqk,bhkd->bhqd", p, v)
```

```cpp
#include <cuda.h>
#include <cuda_bf16.h>
#include <cuda_runtime.h>
#include <stdint.h>

namespace {

constexpr int kRows = 32768;
constexpr int kTilesPerCta = 2;
constexpr int kNumCtas = 128;
constexpr int kSlotBytes = 32768;
constexpr int kNumSlots = 5;
constexpr int kItemsPerTile = 16;
constexpr int kNumItems = kItemsPerTile * kTilesPerCta;

constexpr int kSmemQ = 0;
constexpr int kSmemRing = 65536;
constexpr int kSmemBar = kSmemRing + kNumSlots * kSlotBytes;
constexpr int kSmemBytes = kSmemBar + 256;

constexpr int kBarFull = 0;
constexpr int kBarEmpty = 40;
constexpr int kBarQFull = 80;
constexpr int kBarQEmpty = 96;
constexpr int kBarStageOk = 112;

constexpr int kNamedTurn = 1;
constexpr int kNamedStore = 3;

constexpr float kScaleLog2 = 0.0625f * 1.4426950408889634f;

__device__ __forceinline__ uint32_t smem_u32(const void* p) { return (uint32_t)__cvta_generic_to_shared(p); }

__device__ __forceinline__ void mbar_init(uint32_t bar, uint32_t count) {
    asm volatile("mbarrier.init.shared::cta.b64 [%0], %1;" ::"r"(bar), "r"(count) : "memory");
}
__device__ __forceinline__ void mbar_expect_tx(uint32_t bar, uint32_t bytes) {
    asm volatile("mbarrier.arrive.expect_tx.shared::cta.b64 _, [%0], %1;" ::"r"(bar), "r"(bytes) : "memory");
}
__device__ __forceinline__ void mbar_arrive(uint32_t bar) {
    asm volatile("mbarrier.arrive.shared::cta.b64 _, [%0];" ::"r"(bar) : "memory");
}
__device__ __forceinline__ void mbar_arrive_cta(uint32_t bar, uint32_t cta) {
    asm volatile(
        "{\n.reg .b32 ra;\nmapa.shared::cluster.u32 ra, %0, %1;\n"
        "mbarrier.arrive.shared::cluster.b64 _, [ra];\n}\n" ::"r"(bar), "r"(cta) : "memory");
}
__device__ __forceinline__ void mbar_wait(uint32_t bar, uint32_t parity) {
    asm volatile(
        "{\n.reg .pred p;\n"
        "LAB_WAIT:\n"
        "mbarrier.try_wait.parity.shared::cta.b64 p, [%0], %1;\n"
        "@p bra LAB_DONE;\n"
        "bra LAB_WAIT;\n"
        "LAB_DONE:\n}\n" ::"r"(bar), "r"(parity) : "memory");
}
__device__ __forceinline__ void named_sync(int id, int n) { asm volatile("bar.sync %0, %1;" ::"r"(id), "r"(n) : "memory"); }
__device__ __forceinline__ void named_arrive(int id, int n) { asm volatile("bar.arrive %0, %1;" ::"r"(id), "r"(n) : "memory"); }

__device__ __forceinline__ void tma_load(uint32_t dst, const CUtensorMap* map, uint32_t bar, int row, int chunk) {
    asm volatile(
        "cp.async.bulk.tensor.3d.shared::cluster.global.mbarrier::complete_tx::bytes [%0], [%1, {%3, %4, %5}], [%2];"
        ::"r"(dst), "l"(map), "r"(bar), "r"(0), "r"(row), "r"(chunk) : "memory");
}
__device__ __forceinline__ void tma_load_mc(uint32_t dst, const CUtensorMap* map, uint32_t bar, int row, int chunk) {
    asm volatile(
        "cp.async.bulk.tensor.3d.shared::cluster.global.mbarrier::complete_tx::bytes.multicast::cluster"
        " [%0], [%1, {%3, %4, %5}], [%2], %6;"
        ::"r"(dst), "l"(map), "r"(bar), "r"(0), "r"(row), "r"(chunk), "h"((uint16_t)3) : "memory");
}
__device__ __forceinline__ void tma_store(const CUtensorMap* map, uint32_t src, int row) {
    asm volatile("cp.async.bulk.tensor.3d.global.shared::cta.bulk_group [%0, {%2, %3, %4}], [%1];"
                 ::"l"(map), "r"(src), "r"(0), "r"(row), "r"(0) : "memory");
}
__device__ __forceinline__ void prefetch_map(const CUtensorMap* map) {
    asm volatile("prefetch.tensormap [%0];" ::"l"(map) : "memory");
}
__device__ __forceinline__ void wgmma_fence() { asm volatile("wgmma.fence.sync.aligned;" ::: "memory"); }
__device__ __forceinline__ void wgmma_commit() { asm volatile("wgmma.commit_group.sync.aligned;" ::: "memory"); }
template <int N>
__device__ __forceinline__ void wgmma_wait() { asm volatile("wgmma.wait_group.sync.aligned %0;" ::"n"(N) : "memory"); }

template <int N>
__device__ __forceinline__ void pin_regs(float (&r)[N]) {
#pragma unroll
    for (int i = 0; i < N; ++i) asm volatile("" : "+f"(r[i])::"memory");
}

__device__ __forceinline__ float ex2(float x) {
    float y;
    asm("ex2.approx.ftz.f32 %0, %1;" : "=f"(y) : "f"(x));
    return y;
}
__device__ __forceinline__ uint32_t pack_bf16(float lo, float hi) {
    uint32_t r;
    asm("cvt.rn.bf16x2.f32 %0, %1, %2;" : "=r"(r) : "f"(hi), "f"(lo));
    return r;
}

__device__ __forceinline__ uint64_t make_desc(uint32_t addr, uint32_t lbo_bytes) {
    return (uint64_t)((addr & 0x3FFFF) >> 4) | ((uint64_t)(lbo_bytes >> 4) << 16) | ((uint64_t)(1024 >> 4) << 32) |
           ((uint64_t)1 << 62);
}

__device__ __forceinline__ void wgmma_ss_n128(float (&d)[64], uint64_t desc_a, uint64_t desc_b, int accumulate) {
    asm volatile(
        "{\n.reg .pred p;\nsetp.ne.b32 p, %66, 0;\n"
        "wgmma.mma_async.sync.aligned.m64n128k16.f32.bf16.bf16 {"
        "%0, %1, %2, %3, %4, %5, %6, %7, %8, %9, %10, %11, %12, %13, %14, %15, "
        "%16, %17, %18, %19, %20, %21, %22, %23, %24, %25, %26, %27, %28, %29, %30, %31, "
        "%32, %33, %34, %35, %36, %37, %38, %39, %40, %41, %42, %43, %44, %45, %46, %47, "
        "%48, %49, %50, %51, %52, %53, %54, %55, %56, %57, %58, %59, %60, %61, %62, %63"
        "}, %64, %65, p, 1, 1, 0, 0;\n}\n"
        :
        "+f"(d[0]), "+f"(d[1]), "+f"(d[2]), "+f"(d[3]), "+f"(d[4]), "+f"(d[5]), "+f"(d[6]), "+f"(d[7]),
        "+f"(d[8]), "+f"(d[9]), "+f"(d[10]), "+f"(d[11]), "+f"(d[12]), "+f"(d[13]), "+f"(d[14]), "+f"(d[15]),
        "+f"(d[16]), "+f"(d[17]), "+f"(d[18]), "+f"(d[19]), "+f"(d[20]), "+f"(d[21]), "+f"(d[22]), "+f"(d[23]),
        "+f"(d[24]), "+f"(d[25]), "+f"(d[26]), "+f"(d[27]), "+f"(d[28]), "+f"(d[29]), "+f"(d[30]), "+f"(d[31]),
        "+f"(d[32]), "+f"(d[33]), "+f"(d[34]), "+f"(d[35]), "+f"(d[36]), "+f"(d[37]), "+f"(d[38]), "+f"(d[39]),
        "+f"(d[40]), "+f"(d[41]), "+f"(d[42]), "+f"(d[43]), "+f"(d[44]), "+f"(d[45]), "+f"(d[46]), "+f"(d[47]),
        "+f"(d[48]), "+f"(d[49]), "+f"(d[50]), "+f"(d[51]), "+f"(d[52]), "+f"(d[53]), "+f"(d[54]), "+f"(d[55]),
        "+f"(d[56]), "+f"(d[57]), "+f"(d[58]), "+f"(d[59]), "+f"(d[60]), "+f"(d[61]), "+f"(d[62]), "+f"(d[63])
        : "l"(desc_a), "l"(desc_b), "r"(accumulate));
}

__device__ __forceinline__ void wgmma_rs_n256(float (&d)[128], uint32_t a0, uint32_t a1, uint32_t a2, uint32_t a3,
                                              uint64_t desc_b, int accumulate) {
    asm volatile(
        "{\n.reg .pred p;\nsetp.ne.b32 p, %133, 0;\n"
        "wgmma.mma_async.sync.aligned.m64n256k16.f32.bf16.bf16 {"
        "%0, %1, %2, %3, %4, %5, %6, %7, %8, %9, %10, %11, %12, %13, %14, %15, "
        "%16, %17, %18, %19, %20, %21, %22, %23, %24, %25, %26, %27, %28, %29, %30, %31, "
        "%32, %33, %34, %35, %36, %37, %38, %39, %40, %41, %42, %43, %44, %45, %46, %47, "
        "%48, %49, %50, %51, %52, %53, %54, %55, %56, %57, %58, %59, %60, %61, %62, %63, "
        "%64, %65, %66, %67, %68, %69, %70, %71, %72, %73, %74, %75, %76, %77, %78, %79, "
        "%80, %81, %82, %83, %84, %85, %86, %87, %88, %89, %90, %91, %92, %93, %94, %95, "
        "%96, %97, %98, %99, %100, %101, %102, %103, %104, %105, %106, %107, %108, %109, %110, %111, "
        "%112, %113, %114, %115, %116, %117, %118, %119, %120, %121, %122, %123, %124, %125, %126, %127"
        "}, {%128, %129, %130, %131}, %132, p, 1, 1, 1;\n}\n"
        :
        "+f"(d[0]), "+f"(d[1]), "+f"(d[2]), "+f"(d[3]), "+f"(d[4]), "+f"(d[5]), "+f"(d[6]), "+f"(d[7]),
        "+f"(d[8]), "+f"(d[9]), "+f"(d[10]), "+f"(d[11]), "+f"(d[12]), "+f"(d[13]), "+f"(d[14]), "+f"(d[15]),
        "+f"(d[16]), "+f"(d[17]), "+f"(d[18]), "+f"(d[19]), "+f"(d[20]), "+f"(d[21]), "+f"(d[22]), "+f"(d[23]),
        "+f"(d[24]), "+f"(d[25]), "+f"(d[26]), "+f"(d[27]), "+f"(d[28]), "+f"(d[29]), "+f"(d[30]), "+f"(d[31]),
        "+f"(d[32]), "+f"(d[33]), "+f"(d[34]), "+f"(d[35]), "+f"(d[36]), "+f"(d[37]), "+f"(d[38]), "+f"(d[39]),
        "+f"(d[40]), "+f"(d[41]), "+f"(d[42]), "+f"(d[43]), "+f"(d[44]), "+f"(d[45]), "+f"(d[46]), "+f"(d[47]),
        "+f"(d[48]), "+f"(d[49]), "+f"(d[50]), "+f"(d[51]), "+f"(d[52]), "+f"(d[53]), "+f"(d[54]), "+f"(d[55]),
        "+f"(d[56]), "+f"(d[57]), "+f"(d[58]), "+f"(d[59]), "+f"(d[60]), "+f"(d[61]), "+f"(d[62]), "+f"(d[63]),
        "+f"(d[64]), "+f"(d[65]), "+f"(d[66]), "+f"(d[67]), "+f"(d[68]), "+f"(d[69]), "+f"(d[70]), "+f"(d[71]),
        "+f"(d[72]), "+f"(d[73]), "+f"(d[74]), "+f"(d[75]), "+f"(d[76]), "+f"(d[77]), "+f"(d[78]), "+f"(d[79]),
        "+f"(d[80]), "+f"(d[81]), "+f"(d[82]), "+f"(d[83]), "+f"(d[84]), "+f"(d[85]), "+f"(d[86]), "+f"(d[87]),
        "+f"(d[88]), "+f"(d[89]), "+f"(d[90]), "+f"(d[91]), "+f"(d[92]), "+f"(d[93]), "+f"(d[94]), "+f"(d[95]),
        "+f"(d[96]), "+f"(d[97]), "+f"(d[98]), "+f"(d[99]), "+f"(d[100]), "+f"(d[101]), "+f"(d[102]), "+f"(d[103]),
        "+f"(d[104]), "+f"(d[105]), "+f"(d[106]), "+f"(d[107]), "+f"(d[108]), "+f"(d[109]), "+f"(d[110]), "+f"(d[111]),
        "+f"(d[112]), "+f"(d[113]), "+f"(d[114]), "+f"(d[115]), "+f"(d[116]), "+f"(d[117]), "+f"(d[118]), "+f"(d[119]),
        "+f"(d[120]), "+f"(d[121]), "+f"(d[122]), "+f"(d[123]), "+f"(d[124]), "+f"(d[125]), "+f"(d[126]), "+f"(d[127])
        : "r"(a0), "r"(a1), "r"(a2), "r"(a3), "l"(desc_b), "r"(accumulate));
}


struct Ring {
    uint32_t slot, phase;
    __device__ __forceinline__ void advance() {
        if (++slot == kNumSlots) { slot = 0; phase ^= 1; }
    }
};

__global__ void __cluster_dims__(2, 1, 1) __launch_bounds__(384, 1)
gqa_fwd_kernel(const __grid_constant__ CUtensorMap map_q, const __grid_constant__ CUtensorMap map_k,
               const __grid_constant__ CUtensorMap map_v, const __grid_constant__ CUtensorMap map_o) {
    extern __shared__ __align__(1024) uint8_t smem_raw[];
    const uint32_t smem = smem_u32(smem_raw);
    const uint32_t bars = smem + kSmemBar;
    const int tid = threadIdx.x;
    const int wg = tid >> 7;
    const uint32_t cta_rank = blockIdx.x & 1;

    if (tid == 256) {
        prefetch_map(&map_q);
        prefetch_map(&map_k);
        prefetch_map(&map_v);
        prefetch_map(&map_o);
        for (int s = 0; s < kNumSlots; ++s) {
            mbar_init(bars + kBarFull + 8 * s, 1);
            mbar_init(bars + kBarEmpty + 8 * s, 4);
        }
        for (int w = 0; w < 2; ++w) {
            mbar_init(bars + kBarQFull + 8 * w, 1);
            mbar_init(bars + kBarQEmpty + 8 * w, 1);
            mbar_init(bars + kBarStageOk + 8 * w, 1);
        }
        asm volatile("fence.mbarrier_init.release.cluster;" ::: "memory");
    }
    __syncthreads();
    asm volatile("barrier.cluster.arrive.release.aligned;\nbarrier.cluster.wait.acquire.aligned;" ::: "memory");

    if (wg == 2) {
        asm volatile("setmaxnreg.dec.sync.aligned.u32 24;");
        const int warp = (tid >> 5) & 3;
        if (warp == 0 && (tid & 31) == 0) {
            auto load_q = [&](int t, int w) {
                const uint32_t bar = bars + kBarQFull + 8 * w;
                mbar_expect_tx(bar, 32768);
                tma_load(smem + kSmemQ + w * 32768, &map_q, bar, (t * kNumCtas + blockIdx.x) * 128 + w * 64, 0);
            };
            Ring r{0, 1};
#pragma unroll 1
            for (int i = 0; i < kNumItems; ++i) {
                if (i == 0) load_q(0, 0);
                if (i == 2) load_q(0, 1);
                if (i == kItemsPerTile + 1) { mbar_wait(bars + kBarQEmpty, 0); load_q(1, 0); }
                if (i == kItemsPerTile + 2) { mbar_wait(bars + kBarQEmpty + 8, 0); load_q(1, 1); }
                const int t = i >> 4, j = (i >> 2) & 3, kind = i & 3;
                const int kv_row = (((t * kNumCtas + blockIdx.x) >> 2) << 9) + j * 128;
                const uint32_t full = bars + kBarFull + 8 * r.slot;
                const uint32_t dst = smem + kSmemRing + r.slot * kSlotBytes + cta_rank * 16384;
                mbar_wait(bars + kBarEmpty + 8 * r.slot, r.phase);
                mbar_expect_tx(full, kSlotBytes);
                if (kind < 2) tma_load_mc(dst, &map_k, full, kv_row, kind * 2 + cta_rank);
                else          tma_load_mc(dst, &map_v, full, kv_row + (kind - 2) * 64, cta_rank * 2);
                r.advance();
            }
        } else if (warp == 1) {
#pragma unroll 1
            for (int n = 0; n < 2 * kTilesPerCta; ++n) {
                const int t = n >> 1, w = n & 1;
                const int slot = (t * kItemsPerTile + 14 + w) % kNumSlots;
                named_sync(kNamedStore + w, 160);
                if ((tid & 31) == 0) {
                    tma_store(&map_o, smem + kSmemRing + slot * kSlotBytes, (t * kNumCtas + blockIdx.x) * 128 + w * 64);
                    asm volatile("cp.async.bulk.commit_group;" ::: "memory");
                    asm volatile("cp.async.bulk.wait_group.read 0;" ::: "memory");
                    if (t + 1 < kTilesPerCta) {
                        mbar_arrive_cta(bars + kBarEmpty + 8 * slot, 0);
                        mbar_arrive_cta(bars + kBarEmpty + 8 * slot, 1);
                    }
                }
                __syncwarp();
            }
        }
    } else {
        asm volatile("setmaxnreg.inc.sync.aligned.u32 240;");
        const int lane = tid & 31;
        const int wtid = tid & 127;
        const int my_turn = kNamedTurn + wg, other_turn = kNamedTurn + (wg ^ 1);
        const uint64_t desc_q = make_desc(smem + kSmemQ + wg * 32768, 16);
        const uint64_t desc_k0 = make_desc(smem + kSmemRing, 16);
        const uint64_t desc_v0 = make_desc(smem + kSmemRing, 8192);

        auto release = [&](uint32_t slot) {
            if (wtid < 2) mbar_arrive_cta(bars + kBarEmpty + 8 * slot, wtid);
        };

        if (wg == 1) named_arrive(kNamedTurn, 256);

        float o[128];
        float m0 = 0.f, m1 = 0.f, l0 = 0.f, l1 = 0.f;
        Ring r{0, 0};
#pragma unroll 1
        for (int it = 0; it < 4 * kTilesPerCta; ++it) {
            const int t = it >> 2, j = it & 3;
            const int item = it * 4;
            if (j == 0) {
                m0 = m1 = -INFINITY;
                l0 = l1 = 0.f;
                mbar_wait(bars + kBarQFull + 8 * wg, t);
            }

            float s[64];
            const uint32_t ka = r.slot, ka_ph = r.phase; r.advance();
            const uint32_t kb = r.slot, kb_ph = r.phase; r.advance();
            const uint32_t va = r.slot, va_ph = r.phase; r.advance();
            const uint32_t vb = r.slot, vb_ph = r.phase; r.advance();

            mbar_wait(bars + kBarFull + 8 * ka, ka_ph);
            named_sync(my_turn, 256);
            wgmma_fence();
            {
                const uint64_t dk = desc_k0 + ka * (kSlotBytes >> 4);
#pragma unroll
                for (int ks = 0; ks < 8; ++ks)
                    wgmma_ss_n128(s, desc_q + (ks >> 2) * (8192 >> 4) + (ks & 3) * 2,
                                  dk + (ks >> 2) * (16384 >> 4) + (ks & 3) * 2, ks != 0);
            }
            wgmma_commit();
            mbar_wait(bars + kBarFull + 8 * kb, kb_ph);
            {
                const uint64_t dk = desc_k0 + kb * (kSlotBytes >> 4);
#pragma unroll
                for (int ks = 0; ks < 8; ++ks)
                    wgmma_ss_n128(s, desc_q + (2 + (ks >> 2)) * (8192 >> 4) + (ks & 3) * 2,
                                  dk + (ks >> 2) * (16384 >> 4) + (ks & 3) * 2, 1);
            }
            wgmma_commit();
            named_arrive(other_turn, 256);
            wgmma_wait<1>();
            if (item + 0 + kNumSlots < kNumItems) release(ka);
            wgmma_wait<0>();
            pin_regs(s);
            if (item + 1 + kNumSlots < kNumItems) release(kb);
            if (j == 3 && t + 1 < kTilesPerCta && wtid == 0) mbar_arrive(bars + kBarQEmpty + 8 * wg);

            float x0 = fmaxf(s[0], s[1]), x1 = fmaxf(s[2], s[3]);
#pragma unroll
            for (int i = 1; i < 16; ++i) {
                x0 = fmaxf(x0, fmaxf(s[4 * i], s[4 * i + 1]));
                x1 = fmaxf(x1, fmaxf(s[4 * i + 2], s[4 * i + 3]));
            }
            x0 = fmaxf(x0, __shfl_xor_sync(0xffffffffu, x0, 1));
            x1 = fmaxf(x1, __shfl_xor_sync(0xffffffffu, x1, 1));
            x0 = fmaxf(x0, __shfl_xor_sync(0xffffffffu, x0, 2));
            x1 = fmaxf(x1, __shfl_xor_sync(0xffffffffu, x1, 2));
            x0 = fmaxf(x0, m0);
            x1 = fmaxf(x1, m1);
            const float a0 = ex2((m0 - x0) * kScaleLog2), a1 = ex2((m1 - x1) * kScaleLog2);
            m0 = x0;
            m1 = x1;
            const float b0 = x0 * kScaleLog2, b1 = x1 * kScaleLog2;
            l0 *= a0;
            l1 *= a1;
            if (j != 0) {
#pragma unroll
                for (int i = 0; i < 32; ++i) {
                    o[4 * i] *= a0;
                    o[4 * i + 1] *= a0;
                    o[4 * i + 2] *= a1;
                    o[4 * i + 3] *= a1;
                }
            }
            uint32_t p[32];
            auto softmax_half = [&](int h) {
#pragma unroll
                for (int i = 8 * h; i < 8 * h + 8; ++i) {
                    const float e0 = ex2(fmaf(s[4 * i], kScaleLog2, -b0));
                    const float e1 = ex2(fmaf(s[4 * i + 1], kScaleLog2, -b0));
                    const float e2 = ex2(fmaf(s[4 * i + 2], kScaleLog2, -b1));
                    const float e3 = ex2(fmaf(s[4 * i + 3], kScaleLog2, -b1));
                    l0 += e0 + e1;
                    l1 += e2 + e3;
                    p[2 * i] = pack_bf16(e0, e1);
                    p[2 * i + 1] = pack_bf16(e2, e3);
                }
            };
            softmax_half(0);

            mbar_wait(bars + kBarFull + 8 * va, va_ph);
            named_sync(my_turn, 256);
            pin_regs(o);
            wgmma_fence();
            {
                const uint64_t dv = desc_v0 + va * (kSlotBytes >> 4);
#pragma unroll
                for (int kk = 0; kk < 4; ++kk)
                    wgmma_rs_n256(o, p[4 * kk], p[4 * kk + 1], p[4 * kk + 2], p[4 * kk + 3], dv + kk * (2048 >> 4),
                                  (kk != 0) || (j != 0));
            }
            wgmma_commit();
            softmax_half(1);
            mbar_wait(bars + kBarFull + 8 * vb, vb_ph);
            wgmma_fence();
            {
                const uint64_t dv = desc_v0 + vb * (kSlotBytes >> 4);
#pragma unroll
                for (int kk = 0; kk < 4; ++kk)
                    wgmma_rs_n256(o, p[16 + 4 * kk], p[16 + 4 * kk + 1], p[16 + 4 * kk + 2], p[16 + 4 * kk + 3],
                                  dv + kk * (2048 >> 4), 1);
            }
            wgmma_commit();
            if (wg == 0 || it + 1 < 4 * kTilesPerCta) named_arrive(other_turn, 256);

            wgmma_wait<1>();
            if (j == 3) {
                if (wg == 1) {
                    if (wtid == 0) mbar_arrive(bars + kBarStageOk);
                    if (item + 2 + kNumSlots < kNumItems) release(va);
                }
            } else if (item + 2 + kNumSlots < kNumItems) {
                release(va);
            }
            wgmma_wait<0>();
            pin_regs(o);
            if (j == 3) {
                if (wg == 0) {
                    if (wtid == 0) mbar_arrive(bars + kBarStageOk + 8);
                    if (item + 3 + kNumSlots < kNumItems) release(vb);
                }
            } else if (item + 3 + kNumSlots < kNumItems) {
                release(vb);
            }

            if (j == 3) {
                l0 += __shfl_xor_sync(0xffffffffu, l0, 1);
                l1 += __shfl_xor_sync(0xffffffffu, l1, 1);
                l0 += __shfl_xor_sync(0xffffffffu, l0, 2);
                l1 += __shfl_xor_sync(0xffffffffu, l1, 2);
                const float i0 = 1.0f / l0, i1 = 1.0f / l1;
                const uint32_t stage = smem + kSmemRing + (wg == 0 ? va : vb) * kSlotBytes;
                const int row = ((wtid >> 5) << 4) + (lane & 7) + (((lane >> 3) & 1) << 3);
                const uint32_t base = stage + row * 128 + ((((lane >> 4) ^ lane) & 7) << 4);
                mbar_wait(bars + kBarStageOk + 8 * wg, t);
#pragma unroll
                for (int i = 0; i < 32; i += 2) {
                    const uint32_t r0 = pack_bf16(o[4 * i] * i0, o[4 * i + 1] * i0);
                    const uint32_t r1 = pack_bf16(o[4 * i + 2] * i1, o[4 * i + 3] * i1);
                    const uint32_t r2 = pack_bf16(o[4 * i + 4] * i0, o[4 * i + 5] * i0);
                    const uint32_t r3 = pack_bf16(o[4 * i + 6] * i1, o[4 * i + 7] * i1);
                    const uint32_t addr = (base ^ ((i & 7) << 4)) + (i >> 3) * 8192;
                    asm volatile("stmatrix.sync.aligned.m8n8.x4.shared.b16 [%0], {%1, %2, %3, %4};"
                                 ::"r"(addr), "r"(r0), "r"(r1), "r"(r2), "r"(r3) : "memory");
                }
                asm volatile("fence.proxy.async.shared::cta;" ::: "memory");
                named_arrive(kNamedStore + wg, 160);
            }
        }
    }
}

typedef CUresult (*EncodeTiledFn)(CUtensorMap*, CUtensorMapDataType, cuuint32_t, void*, const cuuint64_t*,
                                  const cuuint64_t*, const cuuint32_t*, const cuuint32_t*, CUtensorMapInterleave,
                                  CUtensorMapSwizzle, CUtensorMapL2promotion, CUtensorMapFloatOOBfill);

void make_map(EncodeTiledFn enc, CUtensorMap* map, const void* ptr, uint32_t box_rows, uint32_t box_chunks) {
    const cuuint64_t dims[3] = {64, (cuuint64_t)kRows, 4};
    const cuuint64_t strides[2] = {512, 128};
    const cuuint32_t box[3] = {64, box_rows, box_chunks};
    const cuuint32_t estr[3] = {1, 1, 1};
    enc(map, CU_TENSOR_MAP_DATA_TYPE_BFLOAT16, 3, const_cast<void*>(ptr), dims, strides, box, estr,
        CU_TENSOR_MAP_INTERLEAVE_NONE, CU_TENSOR_MAP_SWIZZLE_128B, CU_TENSOR_MAP_L2_PROMOTION_L2_128B,
        CU_TENSOR_MAP_FLOAT_OOB_FILL_NONE);
}

}

extern "C" void kernel_launch(void* const* d_in, const int* in_sizes, int n_in, void* d_out, int out_size) {
    (void)in_sizes; (void)n_in; (void)out_size;
    static EncodeTiledFn enc = nullptr;
    if (!enc) {
        void* fn = nullptr;
        cudaDriverEntryPointQueryResult st;
        cudaGetDriverEntryPoint("cuTensorMapEncodeTiled", &fn, cudaEnableDefault, &st);
        enc = (EncodeTiledFn)fn;
        cudaFuncSetAttribute(gqa_fwd_kernel, cudaFuncAttributeMaxDynamicSharedMemorySize, kSmemBytes);
    }
    CUtensorMap mq, mk, mv, mo;
    make_map(enc, &mq, d_in[0], 64, 4);
    make_map(enc, &mk, d_in[1], 128, 1);
    make_map(enc, &mv, d_in[2], 64, 2);
    make_map(enc, &mo, d_out, 64, 4);
    gqa_fwd_kernel<<<kNumCtas, 384, kSmemBytes, cudaStreamPerThread>>>(mq, mk, mv, mo);
}
```

```cpp
#include <cuda.h>
#include <cuda_bf16.h>
#include <cuda_runtime.h>
#include <stdint.h>

namespace {

constexpr int kRows = 32768;
constexpr int kTilesPerCta = 2;
constexpr int kNumCtas = 128;
constexpr int kSlotBytes = 32768;
constexpr int kNumSlots = 5;
constexpr int kItemsPerTile = 16;
constexpr int kNumItems = kItemsPerTile * kTilesPerCta;

constexpr int kSmemQ = 0;
constexpr int kSmemRing = 65536;
constexpr int kSmemBar = kSmemRing + kNumSlots * kSlotBytes;
constexpr int kSmemBytes = kSmemBar + 256;

constexpr int kBarFull = 0;
constexpr int kBarEmpty = 40;
constexpr int kBarQFull = 80;
constexpr int kBarQEmpty = 112;
constexpr int kBarStageOk = 128;
constexpr int kBarStaged = 144;

constexpr int kBarPrefetchGo = 160;
constexpr int kBarTraceDone = 168;
constexpr int kNamedTurn = 1;

constexpr float kScaleLog2 = 0.0625f * 1.4426950408889634f;
constexpr float kLazyLog2 = 8.0f;
constexpr float kLazyRaw = kLazyLog2 / kScaleLog2;

#define PF_Q0 9
#define STAGGER 1500
#define PAIR_BY_GPC 1
#define EARLY_FETCH 0
#define START_WINDOW 4

__device__ __forceinline__ uint32_t smem_u32(const void* p) { return (uint32_t)__cvta_generic_to_shared(p); }

__device__ __forceinline__ void mbar_init(uint32_t bar, uint32_t count) {
    asm volatile("mbarrier.init.shared::cta.b64 [%0], %1;" ::"r"(bar), "r"(count) : "memory");
}
__device__ __forceinline__ void mbar_expect_tx(uint32_t bar, uint32_t bytes) {
    asm volatile("mbarrier.arrive.expect_tx.shared::cta.b64 _, [%0], %1;" ::"r"(bar), "r"(bytes) : "memory");
}
__device__ __forceinline__ void mbar_arrive(uint32_t bar) {
    asm volatile("mbarrier.arrive.shared::cta.b64 _, [%0];" ::"r"(bar) : "memory");
}
__device__ __forceinline__ void mbar_arrive_cta(uint32_t bar, uint32_t cta) {
    asm volatile(
        "{\n.reg .b32 ra;\nmapa.shared::cluster.u32 ra, %0, %1;\n"
        "mbarrier.arrive.shared::cluster.b64 _, [ra];\n}\n" ::"r"(bar), "r"(cta) : "memory");
}
__device__ __forceinline__ void mbar_wait(uint32_t bar, uint32_t parity) {
    asm volatile(
        "{\n.reg .pred p;\n"
        "LAB_WAIT:\n"
        "mbarrier.try_wait.parity.shared::cta.b64 p, [%0], %1;\n"
        "@p bra LAB_DONE;\n"
        "bra LAB_WAIT;\n"
        "LAB_DONE:\n}\n" ::"r"(bar), "r"(parity) : "memory");
}
__device__ __forceinline__ void named_sync(int id, int n) { asm volatile("bar.sync %0, %1;" ::"r"(id), "r"(n) : "memory"); }
__device__ __forceinline__ void named_arrive(int id, int n) { asm volatile("bar.arrive %0, %1;" ::"r"(id), "r"(n) : "memory"); }

__device__ __forceinline__ void tma_load(uint32_t dst, const CUtensorMap* map, uint32_t bar, int row, int chunk) {
    asm volatile(
        "cp.async.bulk.tensor.3d.shared::cluster.global.mbarrier::complete_tx::bytes [%0], [%1, {%3, %4, %5}], [%2];"
        ::"r"(dst), "l"(map), "r"(bar), "r"(0), "r"(row), "r"(chunk) : "memory");
}
__device__ __forceinline__ void tma_load_mc(uint32_t dst, const CUtensorMap* map, uint32_t bar, int row, int chunk) {
    asm volatile(
        "cp.async.bulk.tensor.3d.shared::cluster.global.mbarrier::complete_tx::bytes.multicast::cluster"
        " [%0], [%1, {%3, %4, %5}], [%2], %6;"
        ::"r"(dst), "l"(map), "r"(bar), "r"(0), "r"(row), "r"(chunk), "h"((uint16_t)3) : "memory");
}
__device__ __forceinline__ void tma_store(const CUtensorMap* map, uint32_t src, int row) {
    asm volatile("cp.async.bulk.tensor.3d.global.shared::cta.bulk_group [%0, {%2, %3, %4}], [%1];"
                 ::"l"(map), "r"(src), "r"(0), "r"(row), "r"(0) : "memory");
    asm volatile("cp.async.bulk.commit_group;" ::: "memory");
}
__device__ __forceinline__ void prefetch_map(const CUtensorMap* map) {
    asm volatile("prefetch.tensormap [%0];" ::"l"(map) : "memory");
}
__device__ __forceinline__ void l2_prefetch(const uint8_t* p, uint32_t bytes) {
    asm volatile("cp.async.bulk.prefetch.L2.global [%0], %1;" ::"l"(p), "r"(bytes) : "memory");
}
__device__ __forceinline__ void l2_localize(const uint8_t* p) {
    uint32_t unused;
    asm volatile("ld.volatile.global.L2::256B.b32 %0, [%1];" : "=r"(unused) : "l"(p) : "memory");
}
__device__ __forceinline__ void wgmma_fence() { asm volatile("wgmma.fence.sync.aligned;" ::: "memory"); }
__device__ __forceinline__ void wgmma_commit() { asm volatile("wgmma.commit_group.sync.aligned;" ::: "memory"); }
template <int N>
__device__ __forceinline__ void wgmma_wait() { asm volatile("wgmma.wait_group.sync.aligned %0;" ::"n"(N) : "memory"); }

template <int N>
__device__ __forceinline__ void pin_regs(float (&r)[N]) {
#pragma unroll
    for (int i = 0; i < N; ++i) asm volatile("" : "+f"(r[i])::"memory");
}

__device__ __forceinline__ float ex2(float x) {
    float y;
    asm("ex2.approx.ftz.f32 %0, %1;" : "=f"(y) : "f"(x));
    return y;
}
__device__ __forceinline__ uint32_t pack_bf16(float lo, float hi) {
    uint32_t r;
    asm("cvt.rn.bf16x2.f32 %0, %1, %2;" : "=r"(r) : "f"(hi), "f"(lo));
    return r;
}

__device__ __forceinline__ uint32_t desc_lo(uint32_t addr, uint32_t lbo_bytes) {
    return ((addr & 0x3FFFF) >> 4) | ((lbo_bytes >> 4) << 16);
}
__device__ __forceinline__ uint64_t desc64(uint32_t lo) {
    uint64_t d;
    asm("mov.b64 %0, {%1, %2};" : "=l"(d) : "r"(lo), "r"(0x40000040u));
    return d;
}

__device__ __forceinline__ void wgmma_ss_n128(float (&d)[64], uint64_t desc_a, uint64_t desc_b, int accumulate) {
    asm volatile(
        "{\n.reg .pred p;\nsetp.ne.b32 p, %66, 0;\n"
        "wgmma.mma_async.sync.aligned.m64n128k16.f32.bf16.bf16 {"
        "%0, %1, %2, %3, %4, %5, %6, %7, %8, %9, %10, %11, %12, %13, %14, %15, "
        "%16, %17, %18, %19, %20, %21, %22, %23, %24, %25, %26, %27, %28, %29, %30, %31, "
        "%32, %33, %34, %35, %36, %37, %38, %39, %40, %41, %42, %43, %44, %45, %46, %47, "
        "%48, %49, %50, %51, %52, %53, %54, %55, %56, %57, %58, %59, %60, %61, %62, %63"
        "}, %64, %65, p, 1, 1, 0, 0;\n}\n"
        :
        "+f"(d[0]), "+f"(d[1]), "+f"(d[2]), "+f"(d[3]), "+f"(d[4]), "+f"(d[5]), "+f"(d[6]), "+f"(d[7]),
        "+f"(d[8]), "+f"(d[9]), "+f"(d[10]), "+f"(d[11]), "+f"(d[12]), "+f"(d[13]), "+f"(d[14]), "+f"(d[15]),
        "+f"(d[16]), "+f"(d[17]), "+f"(d[18]), "+f"(d[19]), "+f"(d[20]), "+f"(d[21]), "+f"(d[22]), "+f"(d[23]),
        "+f"(d[24]), "+f"(d[25]), "+f"(d[26]), "+f"(d[27]), "+f"(d[28]), "+f"(d[29]), "+f"(d[30]), "+f"(d[31]),
        "+f"(d[32]), "+f"(d[33]), "+f"(d[34]), "+f"(d[35]), "+f"(d[36]), "+f"(d[37]), "+f"(d[38]), "+f"(d[39]),
        "+f"(d[40]), "+f"(d[41]), "+f"(d[42]), "+f"(d[43]), "+f"(d[44]), "+f"(d[45]), "+f"(d[46]), "+f"(d[47]),
        "+f"(d[48]), "+f"(d[49]), "+f"(d[50]), "+f"(d[51]), "+f"(d[52]), "+f"(d[53]), "+f"(d[54]), "+f"(d[55]),
        "+f"(d[56]), "+f"(d[57]), "+f"(d[58]), "+f"(d[59]), "+f"(d[60]), "+f"(d[61]), "+f"(d[62]), "+f"(d[63])
        : "l"(desc_a), "l"(desc_b), "r"(accumulate));
}

__device__ __forceinline__ void wgmma_rs_n256(float (&d)[128], uint32_t a0, uint32_t a1, uint32_t a2, uint32_t a3,
                                              uint64_t desc_b, int accumulate) {
    asm volatile(
        "{\n.reg .pred p;\nsetp.ne.b32 p, %133, 0;\n"
        "wgmma.mma_async.sync.aligned.m64n256k16.f32.bf16.bf16 {"
        "%0, %1, %2, %3, %4, %5, %6, %7, %8, %9, %10, %11, %12, %13, %14, %15, "
        "%16, %17, %18, %19, %20, %21, %22, %23, %24, %25, %26, %27, %28, %29, %30, %31, "
        "%32, %33, %34, %35, %36, %37, %38, %39, %40, %41, %42, %43, %44, %45, %46, %47, "
        "%48, %49, %50, %51, %52, %53, %54, %55, %56, %57, %58, %59, %60, %61, %62, %63, "
        "%64, %65, %66, %67, %68, %69, %70, %71, %72, %73, %74, %75, %76, %77, %78, %79, "
        "%80, %81, %82, %83, %84, %85, %86, %87, %88, %89, %90, %91, %92, %93, %94, %95, "
        "%96, %97, %98, %99, %100, %101, %102, %103, %104, %105, %106, %107, %108, %109, %110, %111, "
        "%112, %113, %114, %115, %116, %117, %118, %119, %120, %121, %122, %123, %124, %125, %126, %127"
        "}, {%128, %129, %130, %131}, %132, p, 1, 1, 1;\n}\n"
        :
        "+f"(d[0]), "+f"(d[1]), "+f"(d[2]), "+f"(d[3]), "+f"(d[4]), "+f"(d[5]), "+f"(d[6]), "+f"(d[7]),
        "+f"(d[8]), "+f"(d[9]), "+f"(d[10]), "+f"(d[11]), "+f"(d[12]), "+f"(d[13]), "+f"(d[14]), "+f"(d[15]),
        "+f"(d[16]), "+f"(d[17]), "+f"(d[18]), "+f"(d[19]), "+f"(d[20]), "+f"(d[21]), "+f"(d[22]), "+f"(d[23]),
        "+f"(d[24]), "+f"(d[25]), "+f"(d[26]), "+f"(d[27]), "+f"(d[28]), "+f"(d[29]), "+f"(d[30]), "+f"(d[31]),
        "+f"(d[32]), "+f"(d[33]), "+f"(d[34]), "+f"(d[35]), "+f"(d[36]), "+f"(d[37]), "+f"(d[38]), "+f"(d[39]),
        "+f"(d[40]), "+f"(d[41]), "+f"(d[42]), "+f"(d[43]), "+f"(d[44]), "+f"(d[45]), "+f"(d[46]), "+f"(d[47]),
        "+f"(d[48]), "+f"(d[49]), "+f"(d[50]), "+f"(d[51]), "+f"(d[52]), "+f"(d[53]), "+f"(d[54]), "+f"(d[55]),
        "+f"(d[56]), "+f"(d[57]), "+f"(d[58]), "+f"(d[59]), "+f"(d[60]), "+f"(d[61]), "+f"(d[62]), "+f"(d[63]),
        "+f"(d[64]), "+f"(d[65]), "+f"(d[66]), "+f"(d[67]), "+f"(d[68]), "+f"(d[69]), "+f"(d[70]), "+f"(d[71]),
        "+f"(d[72]), "+f"(d[73]), "+f"(d[74]), "+f"(d[75]), "+f"(d[76]), "+f"(d[77]), "+f"(d[78]), "+f"(d[79]),
        "+f"(d[80]), "+f"(d[81]), "+f"(d[82]), "+f"(d[83]), "+f"(d[84]), "+f"(d[85]), "+f"(d[86]), "+f"(d[87]),
        "+f"(d[88]), "+f"(d[89]), "+f"(d[90]), "+f"(d[91]), "+f"(d[92]), "+f"(d[93]), "+f"(d[94]), "+f"(d[95]),
        "+f"(d[96]), "+f"(d[97]), "+f"(d[98]), "+f"(d[99]), "+f"(d[100]), "+f"(d[101]), "+f"(d[102]), "+f"(d[103]),
        "+f"(d[104]), "+f"(d[105]), "+f"(d[106]), "+f"(d[107]), "+f"(d[108]), "+f"(d[109]), "+f"(d[110]), "+f"(d[111]),
        "+f"(d[112]), "+f"(d[113]), "+f"(d[114]), "+f"(d[115]), "+f"(d[116]), "+f"(d[117]), "+f"(d[118]), "+f"(d[119]),
        "+f"(d[120]), "+f"(d[121]), "+f"(d[122]), "+f"(d[123]), "+f"(d[124]), "+f"(d[125]), "+f"(d[126]), "+f"(d[127])
        : "r"(a0), "r"(a1), "r"(a2), "r"(a3), "l"(desc_b), "r"(accumulate));
}

__device__ __forceinline__ void wgmma_rs_n256_x4(float (&d)[128], const uint32_t* a, uint32_t desc_lo, int accumulate,
                                                 int again) {
    asm volatile(
        "{\n.reg .pred p, q, t;\n.reg .b32 lo;\n.reg .b64 d0, d1, d2, d3;\n"
        "setp.ne.b32 p, %145, 0;\nsetp.ne.b32 q, %146, 0;\nsetp.eq.b32 t, 0, 0;\n"
        "mov.b64 d0, {%144, 0x40000040};\n"
        "add.u32 lo, %144, 128;\nmov.b64 d1, {lo, 0x40000040};\n"
        "add.u32 lo, %144, 256;\nmov.b64 d2, {lo, 0x40000040};\n"
        "add.u32 lo, %144, 384;\nmov.b64 d3, {lo, 0x40000040};\n"
        "GROUP:\n"
        "wgmma.fence.sync.aligned;\n"
        "wgmma.mma_async.sync.aligned.m64n256k16.f32.bf16.bf16 {"
        "%0, %1, %2, %3, %4, %5, %6, %7, %8, %9, %10, %11, %12, %13, %14, %15, "
        "%16, %17, %18, %19, %20, %21, %22, %23, %24, %25, %26, %27, %28, %29, %30, %31, "
        "%32, %33, %34, %35, %36, %37, %38, %39, %40, %41, %42, %43, %44, %45, %46, %47, "
        "%48, %49, %50, %51, %52, %53, %54, %55, %56, %57, %58, %59, %60, %61, %62, %63, "
        "%64, %65, %66, %67, %68, %69, %70, %71, %72, %73, %74, %75, %76, %77, %78, %79, "
        "%80, %81, %82, %83, %84, %85, %86, %87, %88, %89, %90, %91, %92, %93, %94, %95, "
        "%96, %97, %98, %99, %100, %101, %102, %103, %104, %105, %106, %107, %108, %109, %110, %111, "
        "%112, %113, %114, %115, %116, %117, %118, %119, %120, %121, %122, %123, %124, %125, %126, %127"
        "}, {%636, %637, %638, %639}, d127, t, 1, 1, 1;\n"
        "wgmma.mma_async.sync.aligned.m64n256k16.f32.bf16.bf16 {"
        "%0, %1, %2, %3, %4, %5, %6, %7, %8, %9, %10, %11, %12, %13, %14, %15, "
        "%16, %17, %18, %19, %20, %21, %22, %23, %24, %25, %26, %27, %28, %29, %30, %31, "
        "%32, %33, %34, %35, %36, %37, %38, %39, %40, %41, %42, %43, %44, %45, %46, %47, "
        "%48, %49, %50, %51, %52, %53, %54, %55, %56, %57, %58, %59, %60, %61, %62, %63, "
        "%64, %65, %66, %67, %68, %69, %70, %71, %72, %73, %74, %75, %76, %77, %78, %79, "
        "%80, %81, %82, %83, %84, %85, %86, %87, %88, %89, %90, %91, %92, %93, %94, %95, "
        "%96, %97, %98, %99, %100, %101, %102, %103, %104, %105, %106, %107, %108, %109, %110, %111, "
        "%112, %113, %114, %115, %116, %117, %118, %119, %120, %121, %122, %123, %124, %125, %126, %127"
        "}, {%636, %637, %638, %639}, d127, t, 1, 1, 1;\n"
        "wgmma.mma_async.sync.aligned.m64n256k16.f32.bf16.bf16 {"
        "%0, %1, %2, %3, %4, %5, %6, %7, %8, %9, %10, %11, %12, %13, %14, %15, "
        "%16, %17, %18, %19, %20, %21, %22, %23, %24, %25, %26, %27, %28, %29, %30, %31, "
        "%32, %33, %34, %35, %36, %37, %38, %39, %40, %41, %42, %43, %44, %45, %46, %47, "
        "%48, %49, %50, %51, %52, %53, %54, %55, %56, %57, %58, %59, %60, %61, %62, %63, "
        "%64, %65, %66, %67, %68, %69, %70, %71, %72, %73, %74, %75, %76, %77, %78, %79, "
        "%80, %81, %82, %83, %84, %85, %86, %87, %88, %89, %90, %91, %92, %93, %94, %95, "
        "%96, %97, %98, %99, %100, %101, %102, %103, %104, %105, %106, %107, %108, %109, %110, %111, "
        "%112, %113, %114, %115, %116, %117, %118, %119, %120, %121, %122, %123, %124, %125, %126, %127"
        "}, {%636, %637, %638, %639}, d127, t, 1, 1, 1;\n"
        "wgmma.mma_async.sync.aligned.m64n256k16.f32.bf16.bf16 {"
        "%0, %1, %2, %3, %4, %5, %6, %7, %8, %9, %10, %11, %12, %13, %14, %15, "
        "%16, %17, %18, %19, %20, %21, %22, %23, %24, %25, %26, %27, %28, %29, %30, %31, "
        "%32, %33, %34, %35, %36, %37, %38, %39, %40, %41, %42, %43, %44, %45, %46, %47, "
        "%48, %49, %50, %51, %52, %53, %54, %55, %56, %57, %58, %59, %60, %61, %62, %63, "
        "%64, %65, %66, %67, %68, %69, %70, %71, %72, %73, %74, %75, %76, %77, %78, %79, "
        "%80, %81, %82, %83, %84, %85, %86, %87, %88, %89, %90, %91, %92, %93, %94, %95, "
        "%96, %97, %98, %99, %100, %101, %102, %103, %104, %105, %106, %107, %108, %109, %110, %111, "
        "%112, %113, %114, %115, %116, %117, %118, %119, %120, %121, %122, %123, %124, %125, %126, %127"
        "}, {%636, %637, %638, %639}, d127, t, 1, 1, 1;\n"
        "wgmma.commit_group.sync.aligned;\n"
        "@q bra GROUP;\n}\n"
        :
        "+f"(d[0]), "+f"(d[1]), "+f"(d[2]), "+f"(d[3]), "+f"(d[4]), "+f"(d[5]), "+f"(d[6]), "+f"(d[7]),
        "+f"(d[8]), "+f"(d[9]), "+f"(d[10]), "+f"(d[11]), "+f"(d[12]), "+f"(d[13]), "+f"(d[14]), "+f"(d[15]),
        "+f"(d[16]), "+f"(d[17]), "+f"(d[18]), "+f"(d[19]), "+f"(d[20]), "+f"(d[21]), "+f"(d[22]), "+f"(d[23]),
        "+f"(d[24]), "+f"(d[25]), "+f"(d[26]), "+f"(d[27]), "+f"(d[28]), "+f"(d[29]), "+f"(d[30]), "+f"(d[31]),
        "+f"(d[32]), "+f"(d[33]), "+f"(d[34]), "+f"(d[35]), "+f"(d[36]), "+f"(d[37]), "+f"(d[38]), "+f"(d[39]),
        "+f"(d[40]), "+f"(d[41]), "+f"(d[42]), "+f"(d[43]), "+f"(d[44]), "+f"(d[45]), "+f"(d[46]), "+f"(d[47]),
        "+f"(d[48]), "+f"(d[49]), "+f"(d[50]), "+f"(d[51]), "+f"(d[52]), "+f"(d[53]), "+f"(d[54]), "+f"(d[55]),
        "+f"(d[56]), "+f"(d[57]), "+f"(d[58]), "+f"(d[59]), "+f"(d[60]), "+f"(d[61]), "+f"(d[62]), "+f"(d[63]),
        "+f"(d[64]), "+f"(d[65]), "+f"(d[66]), "+f"(d[67]), "+f"(d[68]), "+f"(d[69]), "+f"(d[70]), "+f"(d[71]),
        "+f"(d[72]), "+f"(d[73]), "+f"(d[74]), "+f"(d[75]), "+f"(d[76]), "+f"(d[77]), "+f"(d[78]), "+f"(d[79]),
        "+f"(d[80]), "+f"(d[81]), "+f"(d[82]), "+f"(d[83]), "+f"(d[84]), "+f"(d[85]), "+f"(d[86]), "+f"(d[87]),
        "+f"(d[88]), "+f"(d[89]), "+f"(d[90]), "+f"(d[91]), "+f"(d[92]), "+f"(d[93]), "+f"(d[94]), "+f"(d[95]),
        "+f"(d[96]), "+f"(d[97]), "+f"(d[98]), "+f"(d[99]), "+f"(d[100]), "+f"(d[101]), "+f"(d[102]), "+f"(d[103]),
        "+f"(d[104]), "+f"(d[105]), "+f"(d[106]), "+f"(d[107]), "+f"(d[108]), "+f"(d[109]), "+f"(d[110]), "+f"(d[111]),
        "+f"(d[112]), "+f"(d[113]), "+f"(d[114]), "+f"(d[115]), "+f"(d[116]), "+f"(d[117]), "+f"(d[118]), "+f"(d[119]),
        "+f"(d[120]), "+f"(d[121]), "+f"(d[122]), "+f"(d[123]), "+f"(d[124]), "+f"(d[125]), "+f"(d[126]), "+f"(d[127])
        :
        "r"(a[0]), "r"(a[1]), "r"(a[2]), "r"(a[3]), "r"(a[4]), "r"(a[5]), "r"(a[6]), "r"(a[7]),
        "r"(a[8]), "r"(a[9]), "r"(a[10]), "r"(a[11]), "r"(a[12]), "r"(a[13]), "r"(a[14]), "r"(a[15]),
        "r"(desc_lo), "r"(accumulate), "r"(again)
        : "memory");
}

#define TR(role, idx)
#define TRG(role, idx)

struct Ring {
    uint32_t slot, phase;
    __device__ __forceinline__ void advance() {
        if (++slot == kNumSlots) { slot = 0; phase ^= 1; }
    }
};

__device__ __forceinline__ int tile_of_cta(int block) {
    const int c = block >> 1;
    int group, sub;
    if (c < 4)       { group = 30 + ((c == 1 || c == 2) ? 1 : 0); sub = c >> 1; }
    else if (c < 36) { const int u = c - 4;  group = ((u >> 4) << 3) + (u & 7); sub = (u >> 3) & 1; }
    else             { const int u = c - 36; const int h = u >= 14, v = u - 14 * h; sub = v >= 7; group = 16 + 7 * h + v - 7 * sub; }
    return group * 4 + sub * 2 + (block & 1);
}

__global__ void __cluster_dims__(2, 1, 1) __launch_bounds__(384, 1)
gqa_fwd_kernel(const __grid_constant__ CUtensorMap map_q, const __grid_constant__ CUtensorMap map_k,
               const __grid_constant__ CUtensorMap map_v, const __grid_constant__ CUtensorMap map_o,
               const uint8_t* __restrict__ gq, const uint8_t* __restrict__ gk) {
    extern __shared__ __align__(1024) uint8_t smem_raw[];
    const uint32_t smem = smem_u32(smem_raw);
    const uint32_t bars = smem + kSmemBar;
    const int tid = threadIdx.x;
    const int wg = __shfl_sync(0xffffffffu, tid >> 7, 0);
    const uint32_t cta_rank = blockIdx.x & 1;
    const int tile0 = tile_of_cta(blockIdx.x);

    const int group0 = tile0 >> 2;
    const bool late = (group0 < 16) ? (group0 >= 8) : (group0 < 30 ? group0 >= 23 : group0 == 31);
    const long long t_start = clock64();
    if (tid == 256) {
        prefetch_map(&map_q);
        prefetch_map(&map_k);
        prefetch_map(&map_v);
        prefetch_map(&map_o);
        for (int s = 0; s < kNumSlots; ++s) {
            mbar_init(bars + kBarFull + 8 * s, 1);
            mbar_init(bars + kBarEmpty + 8 * s, 4);
        }
        for (int w = 0; w < 2; ++w) {
            mbar_init(bars + kBarQFull + 16 * w, 1);
            mbar_init(bars + kBarQFull + 16 * w + 8, 1);
            mbar_init(bars + kBarQEmpty + 8 * w, 1);
            mbar_init(bars + kBarStageOk + 8 * w, 1);
            mbar_init(bars + kBarStaged + 8 * w, 4);
        }
        mbar_init(bars + kBarPrefetchGo, 1);
        asm volatile("fence.mbarrier_init.release.cluster;" ::: "memory");
    }
    __syncthreads();
    asm volatile("barrier.cluster.arrive.relaxed.aligned;" ::: "memory");

    if (wg == 2) {
        asm volatile("setmaxnreg.dec.sync.aligned.u32 24;");
        const int warp = (tid >> 5) & 3;
        if (warp == 0) {
            auto load_q = [&](int t, int w, int h) {
                const uint32_t bar = bars + kBarQFull + 16 * w + 8 * h;
                mbar_expect_tx(bar, 16384);
                tma_load(smem + kSmemQ + w * 32768 + h * 16384, &map_q, bar,
                         (t * kNumCtas + tile0) * 128 + w * 64, 2 * h);
            };
            auto load_kv = [&](int i, uint32_t slot) {
                const int t = i >> 4, j = (i >> 2) & 3, kind = i & 3;
                const int kv_row = (((t * kNumCtas + tile0) >> 2) << 9) + j * 128;
                const uint32_t full = bars + kBarFull + 8 * slot;
                const uint32_t dst = smem + kSmemRing + slot * kSlotBytes + cta_rank * 16384;
                TR(2, i);
                mbar_expect_tx(full, kSlotBytes);
                if (kind < 2) tma_load_mc(dst, &map_k, full, kv_row, kind * 2 + cta_rank);
                else          tma_load_mc(dst, &map_v, full, kv_row + (kind - 2) * 64, cta_rank * 2);
            };
            const bool leader = (tid & 31) == 0;
            if (late) while (clock64() - t_start < STAGGER) {}
            if (leader) load_q(0, 0, 0);
            __syncwarp();
            asm volatile("barrier.cluster.wait.aligned;" ::: "memory");
            if (leader) {
                auto start_bar = [&](int n) -> uint32_t {
                    if (n == 0) return bars + kBarQFull;
                    if (n == 2) return bars + kBarQFull + 8;
                    if (n == 4) return bars + kBarQFull + 16;
                    if (n == 5) return bars + kBarQFull + 24;
                    return bars + kBarFull + 8 * (n < 4 ? (n >> 1) : (n - 4));
                };
#pragma unroll
                for (int n = 1; n < 9; ++n) {
                    if (n >= START_WINDOW) mbar_wait(start_bar(n - START_WINDOW), 0);
                    if (n == 2) load_q(0, 0, 1);
                    else if (n == 4) load_q(0, 1, 0);
                    else if (n == 5) load_q(0, 1, 1);
                    else load_kv(n < 4 ? (n >> 1) : (n - 4), n < 4 ? (n >> 1) : (n - 4));
                }
                auto store_out = [&](int t, int w) {
                    const uint32_t slot = (t * kItemsPerTile + 14 + w) % kNumSlots;
                    mbar_wait(bars + kBarStaged + 8 * w, t);
                    TR(3, 8 + 2 * t + w);
                    tma_store(&map_o, smem + kSmemRing + slot * kSlotBytes, (t * kNumCtas + tile0) * 128 + w * 64);
                    if (t + 1 < kTilesPerCta) {
                        asm volatile("cp.async.bulk.wait_group.read 0;" ::: "memory");
                        TR(3, w);
                        mbar_arrive_cta(bars + kBarEmpty + 8 * slot, 0);
                        mbar_arrive_cta(bars + kBarEmpty + 8 * slot, 1);
                    }
                };
                Ring r{0, 0};
#pragma unroll 1
                for (int i = kNumSlots; i < kNumItems; ++i) {
                    if (i == PF_Q0) mbar_arrive(bars + kBarPrefetchGo);
                    if (i == kItemsPerTile + 1) { mbar_wait(bars + kBarQEmpty, 0); load_q(1, 0, 0); load_q(1, 0, 1); }
                    if (i == kItemsPerTile + 2) { mbar_wait(bars + kBarQEmpty + 8, 0); load_q(1, 1, 0); load_q(1, 1, 1); }
                    if (i == kItemsPerTile + 3) store_out(0, 0);
                    if (i == kItemsPerTile + 4) store_out(0, 1);
                    mbar_wait(bars + kBarEmpty + 8 * r.slot, r.phase);
                    load_kv(i, r.slot);
                    r.advance();
                }
                store_out(1, 0);
                store_out(1, 1);
                asm volatile("cp.async.bulk.wait_group.read 0;" ::: "memory");
                TR(3, 3);
            }
        } else {
            asm volatile("barrier.cluster.wait.aligned;" ::: "memory");
            if (warp == 1) {
                mbar_wait(bars + kBarPrefetchGo, 0);
#pragma unroll 1
                for (int i = 0; i < 8; ++i)
                    l2_localize(gq + (size_t)(kNumCtas + tile0) * 65536 + i * 8192 + (tid & 31) * 256);
            }
        }
    } else {
        asm volatile("setmaxnreg.inc.sync.aligned.u32 240;");
        asm volatile("barrier.cluster.wait.aligned;" ::: "memory");
        const int lane = tid & 31;
        const int wtid = tid & 127;
        const int my_turn = kNamedTurn + wg, other_turn = kNamedTurn + (wg ^ 1);
        const uint32_t desc_q = desc_lo(smem + kSmemQ + wg * 32768, 16);
        const uint32_t desc_k0 = desc_lo(smem + kSmemRing, 16);
        const uint32_t desc_v0 = desc_lo(smem + kSmemRing, 8192);
        const int never = (int)(reinterpret_cast<uintptr_t>(gq) & 1);

        uint32_t empty_remote;
        asm("mapa.shared::cluster.u32 %0, %1, %2;" : "=r"(empty_remote) : "r"(bars + kBarEmpty), "r"(wtid & 1));
        auto release = [&](uint32_t slot) {
            if (wtid < 2)
                asm volatile("mbarrier.arrive.shared::cluster.b64 _, [%0];" ::"r"(empty_remote + 8 * slot) : "memory");
        };

        if (wg == 1) named_arrive(kNamedTurn, 256);

        float o[128];
        float m0 = 0.f, m1 = 0.f, l0 = 0.f, l1 = 0.f;
        Ring r{0, 0};
#pragma unroll 1
        for (int it = 0; it < 4 * kTilesPerCta; ++it) {
            const int t = it >> 2, j = it & 3;
            const int item = it * 4;

            float s[64];
            const uint32_t ka = r.slot, ka_ph = r.phase; r.advance();
            const uint32_t kb = r.slot, kb_ph = r.phase; r.advance();
            const uint32_t va = r.slot, va_ph = r.phase; r.advance();
            const uint32_t vb = r.slot, vb_ph = r.phase; r.advance();

            if (j == 0) {
                m0 = m1 = -INFINITY;
                l0 = l1 = 0.f;
                mbar_wait(bars + kBarQFull + 16 * wg, t);
            }
            TR(wg, it * 12 + 0);
            mbar_wait(bars + kBarFull + 8 * ka, ka_ph);
            TR(wg, it * 12 + 1);
            named_sync(my_turn, 256);
            wgmma_fence();
            {
                const uint32_t dk = desc_k0 + ka * (kSlotBytes >> 4);
#pragma unroll
                for (int ks = 0; ks < 8; ++ks)
                    wgmma_ss_n128(s, desc64(desc_q + (ks >> 2) * (8192 >> 4) + (ks & 3) * 2),
                                  desc64(dk + (ks >> 2) * (16384 >> 4) + (ks & 3) * 2), ks != 0);
            }
            wgmma_commit();
            if (j == 0) mbar_wait(bars + kBarQFull + 16 * wg + 8, t);
            mbar_wait(bars + kBarFull + 8 * kb, kb_ph);
            {
                const uint32_t dk = desc_k0 + kb * (kSlotBytes >> 4);
#pragma unroll
                for (int ks = 0; ks < 8; ++ks)
                    wgmma_ss_n128(s, desc64(desc_q + (2 + (ks >> 2)) * (8192 >> 4) + (ks & 3) * 2),
                                  desc64(dk + (ks >> 2) * (16384 >> 4) + (ks & 3) * 2), 1);
            }
            wgmma_commit();
            named_arrive(other_turn, 256);
            TR(wg, it * 12 + 3);
            wgmma_wait<1>();
            if (item + 0 + kNumSlots < kNumItems) release(ka);
            wgmma_wait<0>();
            if (item + 1 + kNumSlots < kNumItems) release(kb);
            if (j == 3 && t + 1 < kTilesPerCta && wtid == 0) mbar_arrive(bars + kBarQEmpty + 8 * wg);
            pin_regs(s);
            TR(wg, it * 12 + 4);

            float x0 = fmaxf(s[0], s[1]), x1 = fmaxf(s[2], s[3]);
            float y0 = fmaxf(s[4], s[5]), y1 = fmaxf(s[6], s[7]);
#pragma unroll
            for (int i = 2; i < 16; i += 2) {
                x0 = fmaxf(x0, fmaxf(s[4 * i], s[4 * i + 1]));
                x1 = fmaxf(x1, fmaxf(s[4 * i + 2], s[4 * i + 3]));
                y0 = fmaxf(y0, fmaxf(s[4 * i + 4], s[4 * i + 5]));
                y1 = fmaxf(y1, fmaxf(s[4 * i + 6], s[4 * i + 7]));
            }
            x0 = fmaxf(x0, y0);
            x1 = fmaxf(x1, y1);
            const bool moved = !(x0 <= m0 + kLazyRaw) || !(x1 <= m1 + kLazyRaw);
            if (__any_sync(0xffffffffu, moved)) {
                x0 = fmaxf(x0, __shfl_xor_sync(0xffffffffu, x0, 1));
                x1 = fmaxf(x1, __shfl_xor_sync(0xffffffffu, x1, 1));
                x0 = fmaxf(x0, __shfl_xor_sync(0xffffffffu, x0, 2));
                x1 = fmaxf(x1, __shfl_xor_sync(0xffffffffu, x1, 2));
                x0 = fmaxf(x0, m0);
                x1 = fmaxf(x1, m1);
                const float a0 = ex2((m0 - x0) * kScaleLog2), a1 = ex2((m1 - x1) * kScaleLog2);
                m0 = x0;
                m1 = x1;
                l0 *= a0;
                l1 *= a1;
                if (j != 0) {
#pragma unroll
                    for (int i = 0; i < 32; ++i) {
                        o[4 * i] *= a0;
                        o[4 * i + 1] *= a0;
                        o[4 * i + 2] *= a1;
                        o[4 * i + 3] *= a1;
                    }
                }
            }
            const float b0 = m0 * kScaleLog2, b1 = m1 * kScaleLog2;
            uint32_t p[32];
            auto softmax_half = [&](int h) {
#pragma unroll
                for (int i = 8 * h; i < 8 * h + 8; ++i) {
                    const float e0 = ex2(fmaf(s[4 * i], kScaleLog2, -b0));
                    const float e1 = ex2(fmaf(s[4 * i + 1], kScaleLog2, -b0));
                    const float e2 = ex2(fmaf(s[4 * i + 2], kScaleLog2, -b1));
                    const float e3 = ex2(fmaf(s[4 * i + 3], kScaleLog2, -b1));
                    l0 += e0 + e1;
                    l1 += e2 + e3;
                    p[2 * i] = pack_bf16(e0, e1);
                    p[2 * i + 1] = pack_bf16(e2, e3);
                }
            };
            softmax_half(0);

            TR(wg, it * 12 + 5);
            mbar_wait(bars + kBarFull + 8 * va, va_ph);
            TR(wg, it * 12 + 6);
            named_sync(my_turn, 256);
            wgmma_rs_n256_x4(o, p, desc_v0 + va * (kSlotBytes >> 4), j != 0, never);
            TR(wg, it * 12 + 7);
            softmax_half(1);
            TR(wg, it * 12 + 8);
            mbar_wait(bars + kBarFull + 8 * vb, vb_ph);
            wgmma_rs_n256_x4(o, p + 16, desc_v0 + vb * (kSlotBytes >> 4), 1, never);
            if (wg == 0 || it + 1 < 4 * kTilesPerCta) named_arrive(other_turn, 256);
            TR(wg, it * 12 + 9);

            wgmma_wait<1>();
            if (j == 3) {
                if (wg == 1) {
                    if (wtid == 0) mbar_arrive(bars + kBarStageOk);
                    if (item + 2 + kNumSlots < kNumItems) release(va);
                }
            } else if (item + 2 + kNumSlots < kNumItems) {
                release(va);
            }
            wgmma_wait<0>();
            if (j == 3) {
                if (wg == 0) {
                    if (wtid == 0) mbar_arrive(bars + kBarStageOk + 8);
                    if (item + 3 + kNumSlots < kNumItems) release(vb);
                }
            } else if (item + 3 + kNumSlots < kNumItems) {
                release(vb);
            }
            pin_regs(o);
            TR(wg, it * 12 + 10);

            if (j == 3) {
                l0 += __shfl_xor_sync(0xffffffffu, l0, 1);
                l1 += __shfl_xor_sync(0xffffffffu, l1, 1);
                l0 += __shfl_xor_sync(0xffffffffu, l0, 2);
                l1 += __shfl_xor_sync(0xffffffffu, l1, 2);
                const float i0 = 1.0f / l0, i1 = 1.0f / l1;
                const uint32_t stage = smem + kSmemRing + (wg == 0 ? va : vb) * kSlotBytes;
                const int row = ((wtid >> 5) << 4) + (lane & 7) + (((lane >> 3) & 1) << 3);
                const uint32_t base = stage + row * 128 + ((((lane >> 4) ^ lane) & 7) << 4);
                uint32_t pk[64];
#pragma unroll
                for (int i = 0; i < 32; ++i) {
                    pk[2 * i] = pack_bf16(o[4 * i] * i0, o[4 * i + 1] * i0);
                    pk[2 * i + 1] = pack_bf16(o[4 * i + 2] * i1, o[4 * i + 3] * i1);
                }
                mbar_wait(bars + kBarStageOk + 8 * wg, t);
                TR(wg, it * 12 + 2);
#pragma unroll
                for (int i = 0; i < 32; i += 2) {
                    const uint32_t addr = (base ^ ((i & 7) << 4)) + (i >> 3) * 8192;
                    asm volatile("stmatrix.sync.aligned.m8n8.x4.shared.b16 [%0], {%1, %2, %3, %4};"
                                 ::"r"(addr), "r"(pk[2 * i]), "r"(pk[2 * i + 1]), "r"(pk[2 * i + 2]), "r"(pk[2 * i + 3])
                                 : "memory");
                }
                asm volatile("fence.proxy.async.shared::cta;" ::: "memory");
                __syncwarp();
                if (lane == 0) mbar_arrive(bars + kBarStaged + 8 * wg);
            }
            TR(wg, it * 12 + 11);
        }
    }
}

typedef CUresult (*EncodeTiledFn)(CUtensorMap*, CUtensorMapDataType, cuuint32_t, void*, const cuuint64_t*,
                                  const cuuint64_t*, const cuuint32_t*, const cuuint32_t*, CUtensorMapInterleave,
                                  CUtensorMapSwizzle, CUtensorMapL2promotion, CUtensorMapFloatOOBfill);

void make_map(EncodeTiledFn enc, CUtensorMap* map, const void* ptr, uint32_t box_rows, uint32_t box_chunks) {
    const cuuint64_t dims[3] = {64, (cuuint64_t)kRows, 4};
    const cuuint64_t strides[2] = {512, 128};
    const cuuint32_t box[3] = {64, box_rows, box_chunks};
    const cuuint32_t estr[3] = {1, 1, 1};
    enc(map, CU_TENSOR_MAP_DATA_TYPE_BFLOAT16, 3, const_cast<void*>(ptr), dims, strides, box, estr,
        CU_TENSOR_MAP_INTERLEAVE_NONE, CU_TENSOR_MAP_SWIZZLE_128B, CU_TENSOR_MAP_L2_PROMOTION_L2_128B,
        CU_TENSOR_MAP_FLOAT_OOB_FILL_NONE);
}

}

extern "C" void kernel_launch(void* const* d_in, const int* in_sizes, int n_in, void* d_out, int out_size) {
    (void)in_sizes; (void)n_in; (void)out_size;
    static EncodeTiledFn enc = nullptr;
    if (!enc) {
        void* fn = nullptr;
        cudaDriverEntryPointQueryResult st;
        cudaGetDriverEntryPoint("cuTensorMapEncodeTiled", &fn, cudaEnableDefault, &st);
        enc = (EncodeTiledFn)fn;
        cudaFuncSetAttribute(gqa_fwd_kernel, cudaFuncAttributeMaxDynamicSharedMemorySize, kSmemBytes);
    }
    CUtensorMap mq, mk, mv, mo;
    make_map(enc, &mq, d_in[0], 64, 2);
    make_map(enc, &mk, d_in[1], 128, 1);
    make_map(enc, &mv, d_in[2], 64, 2);
    make_map(enc, &mo, d_out, 64, 4);
    gqa_fwd_kernel<<<kNumCtas, 384, kSmemBytes, cudaStreamPerThread>>>(
        mq, mk, mv, mo, (const uint8_t*)d_in[0], (const uint8_t*)d_in[1]);
}
```

```cpp
#include <cuda.h>
#include <cuda_bf16.h>
#include <cuda_runtime.h>
#include <stdint.h>

namespace {

constexpr int kRows = 32768;
constexpr int kTilesPerCta = 2;
constexpr int kNumCtas = 128;
constexpr int kSlotBytes = 32768;
constexpr int kNumSlots = 5;
constexpr int kItemsPerTile = 16;
constexpr int kNumItems = kItemsPerTile * kTilesPerCta;

constexpr int kSmemQ = 0;
constexpr int kSmemRing = 65536;
constexpr int kSmemBar = kSmemRing + kNumSlots * kSlotBytes;
constexpr int kSmemBytes = kSmemBar + 256;

constexpr int kBarFull = 0;
constexpr int kBarEmpty = 40;
constexpr int kBarQFull = 80;
constexpr int kBarQEmpty = 112;
constexpr int kBarStageOk = 128;
constexpr int kBarStaged = 144;

constexpr int kBarPrefetchGo = 160;
constexpr int kBarTraceDone = 176;
constexpr int kNamedTurn = 1;

constexpr float kScaleLog2 = 0.0625f * 1.4426950408889634f;
constexpr float kLazyLog2 = 8.0f;
constexpr float kLazyRaw = kLazyLog2 / kScaleLog2;
constexpr float kLazySum = 256.0f;

#define PF_Q0 9
#define SM_FIRST 5
#define PV_WAIT_FIRST 1
#define PV_GROUP6 0
#define CHECK_MODE 1
#define PF_KV2 16
#define STAGE_MODE 0
#define STORE_A_FIRST 1
#define FINAL_PERWARP 1
#define STAGGER 1500
#define PAIR_BY_GPC 1
#define EARLY_FETCH 1
#define START_WINDOW 4

__device__ __forceinline__ uint32_t smem_u32(const void* p) { return (uint32_t)__cvta_generic_to_shared(p); }

__device__ __forceinline__ void mbar_init(uint32_t bar, uint32_t count) {
    asm volatile("mbarrier.init.shared::cta.b64 [%0], %1;" ::"r"(bar), "r"(count) : "memory");
}
__device__ __forceinline__ void mbar_expect_tx(uint32_t bar, uint32_t bytes) {
    asm volatile("mbarrier.arrive.expect_tx.shared::cta.b64 _, [%0], %1;" ::"r"(bar), "r"(bytes) : "memory");
}
__device__ __forceinline__ void mbar_arrive(uint32_t bar) {
    asm volatile("mbarrier.arrive.shared::cta.b64 _, [%0];" ::"r"(bar) : "memory");
}
__device__ __forceinline__ void mbar_arrive_cta(uint32_t bar, uint32_t cta) {
    asm volatile(
        "{\n.reg .b32 ra;\nmapa.shared::cluster.u32 ra, %0, %1;\n"
        "mbarrier.arrive.shared::cluster.b64 _, [ra];\n}\n" ::"r"(bar), "r"(cta) : "memory");
}
__device__ __forceinline__ void mbar_wait(uint32_t bar, uint32_t parity) {
    asm volatile(
        "{\n.reg .pred p;\n"
        "LAB_WAIT:\n"
        "mbarrier.try_wait.parity.shared::cta.b64 p, [%0], %1;\n"
        "@p bra LAB_DONE;\n"
        "bra LAB_WAIT;\n"
        "LAB_DONE:\n}\n" ::"r"(bar), "r"(parity) : "memory");
}
__device__ __forceinline__ void named_sync(int id, int n) { asm volatile("bar.sync %0, %1;" ::"r"(id), "r"(n) : "memory"); }
__device__ __forceinline__ void named_arrive(int id, int n) { asm volatile("bar.arrive %0, %1;" ::"r"(id), "r"(n) : "memory"); }

__device__ __forceinline__ void tma_load(uint32_t dst, const CUtensorMap* map, uint32_t bar, int row, int chunk) {
    asm volatile(
        "cp.async.bulk.tensor.3d.shared::cluster.global.mbarrier::complete_tx::bytes [%0], [%1, {%3, %4, %5}], [%2];"
        ::"r"(dst), "l"(map), "r"(bar), "r"(0), "r"(row), "r"(chunk) : "memory");
}
__device__ __forceinline__ void tma_load_mc(uint32_t dst, const CUtensorMap* map, uint32_t bar, int row, int chunk) {
    asm volatile(
        "cp.async.bulk.tensor.3d.shared::cluster.global.mbarrier::complete_tx::bytes.multicast::cluster"
        " [%0], [%1, {%3, %4, %5}], [%2], %6;"
        ::"r"(dst), "l"(map), "r"(bar), "r"(0), "r"(row), "r"(chunk), "h"((uint16_t)3) : "memory");
}
__device__ __forceinline__ void tma_store(const CUtensorMap* map, uint32_t src, int row, int chunk) {
    asm volatile("cp.async.bulk.tensor.3d.global.shared::cta.bulk_group [%0, {%2, %3, %4}], [%1];"
                 ::"l"(map), "r"(src), "r"(0), "r"(row), "r"(chunk) : "memory");
    asm volatile("cp.async.bulk.commit_group;" ::: "memory");
}
__device__ __forceinline__ void prefetch_map(const CUtensorMap* map) {
    asm volatile("prefetch.tensormap [%0];" ::"l"(map) : "memory");
}
__device__ __forceinline__ void l2_prefetch(const uint8_t* p, uint32_t bytes) {
    asm volatile("cp.async.bulk.prefetch.L2.global [%0], %1;" ::"l"(p), "r"(bytes) : "memory");
}
__device__ __forceinline__ void l2_localize(const uint8_t* p) {
    uint32_t unused;
    asm volatile("ld.volatile.global.L2::256B.b32 %0, [%1];" : "=r"(unused) : "l"(p) : "memory");
}
__device__ __forceinline__ void wgmma_fence() { asm volatile("wgmma.fence.sync.aligned;" ::: "memory"); }
__device__ __forceinline__ void wgmma_commit() { asm volatile("wgmma.commit_group.sync.aligned;" ::: "memory"); }
template <int N>
__device__ __forceinline__ void wgmma_wait() { asm volatile("wgmma.wait_group.sync.aligned %0;" ::"n"(N) : "memory"); }

template <int N>
__device__ __forceinline__ void pin_regs(float (&r)[N]) {
#pragma unroll
    for (int i = 0; i < N; ++i) asm volatile("" : "+f"(r[i])::"memory");
}

__device__ __forceinline__ float ex2(float x) {
    float y;
    asm("ex2.approx.ftz.f32 %0, %1;" : "=f"(y) : "f"(x));
    return y;
}
__device__ __forceinline__ float rcp(float x) {
    float y;
    asm("rcp.approx.ftz.f32 %0, %1;" : "=f"(y) : "f"(x));
    return y;
}
__device__ __forceinline__ uint32_t pack_bf16(float lo, float hi) {
    uint32_t r;
    asm("cvt.rn.bf16x2.f32 %0, %1, %2;" : "=r"(r) : "f"(hi), "f"(lo));
    return r;
}

__device__ __forceinline__ bool any_above(const float (&s)[64], float t0, float t1) {
    uint32_t r;
    asm("{\n.reg .pred a, b, c, d;\n"
        "setp.gtu.f32 a, %1, %65;\nsetp.gtu.f32 b, %2, %65;\nsetp.gtu.f32 c, %3, %66;\nsetp.gtu.f32 d, %4, %66;\n"
        "setp.gtu.or.f32 a, %5, %65, a;\nsetp.gtu.or.f32 b, %6, %65, b;\nsetp.gtu.or.f32 c, %7, %66, c;\nsetp.gtu.or.f32 d, %8, %66, d;\n"
        "setp.gtu.or.f32 a, %9, %65, a;\nsetp.gtu.or.f32 b, %10, %65, b;\nsetp.gtu.or.f32 c, %11, %66, c;\nsetp.gtu.or.f32 d, %12, %66, d;\n"
        "setp.gtu.or.f32 a, %13, %65, a;\nsetp.gtu.or.f32 b, %14, %65, b;\nsetp.gtu.or.f32 c, %15, %66, c;\nsetp.gtu.or.f32 d, %16, %66, d;\n"
        "setp.gtu.or.f32 a, %17, %65, a;\nsetp.gtu.or.f32 b, %18, %65, b;\nsetp.gtu.or.f32 c, %19, %66, c;\nsetp.gtu.or.f32 d, %20, %66, d;\n"
        "setp.gtu.or.f32 a, %21, %65, a;\nsetp.gtu.or.f32 b, %22, %65, b;\nsetp.gtu.or.f32 c, %23, %66, c;\nsetp.gtu.or.f32 d, %24, %66, d;\n"
        "setp.gtu.or.f32 a, %25, %65, a;\nsetp.gtu.or.f32 b, %26, %65, b;\nsetp.gtu.or.f32 c, %27, %66, c;\nsetp.gtu.or.f32 d, %28, %66, d;\n"
        "setp.gtu.or.f32 a, %29, %65, a;\nsetp.gtu.or.f32 b, %30, %65, b;\nsetp.gtu.or.f32 c, %31, %66, c;\nsetp.gtu.or.f32 d, %32, %66, d;\n"
        "setp.gtu.or.f32 a, %33, %65, a;\nsetp.gtu.or.f32 b, %34, %65, b;\nsetp.gtu.or.f32 c, %35, %66, c;\nsetp.gtu.or.f32 d, %36, %66, d;\n"
        "setp.gtu.or.f32 a, %37, %65, a;\nsetp.gtu.or.f32 b, %38, %65, b;\nsetp.gtu.or.f32 c, %39, %66, c;\nsetp.gtu.or.f32 d, %40, %66, d;\n"
        "setp.gtu.or.f32 a, %41, %65, a;\nsetp.gtu.or.f32 b, %42, %65, b;\nsetp.gtu.or.f32 c, %43, %66, c;\nsetp.gtu.or.f32 d, %44, %66, d;\n"
        "setp.gtu.or.f32 a, %45, %65, a;\nsetp.gtu.or.f32 b, %46, %65, b;\nsetp.gtu.or.f32 c, %47, %66, c;\nsetp.gtu.or.f32 d, %48, %66, d;\n"
        "setp.gtu.or.f32 a, %49, %65, a;\nsetp.gtu.or.f32 b, %50, %65, b;\nsetp.gtu.or.f32 c, %51, %66, c;\nsetp.gtu.or.f32 d, %52, %66, d;\n"
        "setp.gtu.or.f32 a, %53, %65, a;\nsetp.gtu.or.f32 b, %54, %65, b;\nsetp.gtu.or.f32 c, %55, %66, c;\nsetp.gtu.or.f32 d, %56, %66, d;\n"
        "setp.gtu.or.f32 a, %57, %65, a;\nsetp.gtu.or.f32 b, %58, %65, b;\nsetp.gtu.or.f32 c, %59, %66, c;\nsetp.gtu.or.f32 d, %60, %66, d;\n"
        "setp.gtu.or.f32 a, %61, %65, a;\nsetp.gtu.or.f32 b, %62, %65, b;\nsetp.gtu.or.f32 c, %63, %66, c;\nsetp.gtu.or.f32 d, %64, %66, d;\n"
        "or.pred a, a, b;\nor.pred c, c, d;\nor.pred a, a, c;\nselp.u32 %0, 1, 0, a;\n}\n"
        : "=r"(r)
        :
        "f"(s[0]), "f"(s[1]), "f"(s[2]), "f"(s[3]), "f"(s[4]), "f"(s[5]), "f"(s[6]), "f"(s[7]),
        "f"(s[8]), "f"(s[9]), "f"(s[10]), "f"(s[11]), "f"(s[12]), "f"(s[13]), "f"(s[14]), "f"(s[15]),
        "f"(s[16]), "f"(s[17]), "f"(s[18]), "f"(s[19]), "f"(s[20]), "f"(s[21]), "f"(s[22]), "f"(s[23]),
        "f"(s[24]), "f"(s[25]), "f"(s[26]), "f"(s[27]), "f"(s[28]), "f"(s[29]), "f"(s[30]), "f"(s[31]),
        "f"(s[32]), "f"(s[33]), "f"(s[34]), "f"(s[35]), "f"(s[36]), "f"(s[37]), "f"(s[38]), "f"(s[39]),
        "f"(s[40]), "f"(s[41]), "f"(s[42]), "f"(s[43]), "f"(s[44]), "f"(s[45]), "f"(s[46]), "f"(s[47]),
        "f"(s[48]), "f"(s[49]), "f"(s[50]), "f"(s[51]), "f"(s[52]), "f"(s[53]), "f"(s[54]), "f"(s[55]),
        "f"(s[56]), "f"(s[57]), "f"(s[58]), "f"(s[59]), "f"(s[60]), "f"(s[61]), "f"(s[62]), "f"(s[63]),
        "f"(t0), "f"(t1));
    return r != 0;
}

__device__ __forceinline__ bool upper_half_above(const float (&s)[64], float t0, float t1) {
    uint32_t r;
    asm("{\n.reg .pred a, b, c, d;\n"
        "setp.gtu.f32 a, %1, %33;\nsetp.gtu.f32 b, %2, %33;\nsetp.gtu.f32 c, %3, %34;\nsetp.gtu.f32 d, %4, %34;\n"
        "setp.gtu.or.f32 a, %5, %33, a;\nsetp.gtu.or.f32 b, %6, %33, b;\nsetp.gtu.or.f32 c, %7, %34, c;\nsetp.gtu.or.f32 d, %8, %34, d;\n"
        "setp.gtu.or.f32 a, %9, %33, a;\nsetp.gtu.or.f32 b, %10, %33, b;\nsetp.gtu.or.f32 c, %11, %34, c;\nsetp.gtu.or.f32 d, %12, %34, d;\n"
        "setp.gtu.or.f32 a, %13, %33, a;\nsetp.gtu.or.f32 b, %14, %33, b;\nsetp.gtu.or.f32 c, %15, %34, c;\nsetp.gtu.or.f32 d, %16, %34, d;\n"
        "setp.gtu.or.f32 a, %17, %33, a;\nsetp.gtu.or.f32 b, %18, %33, b;\nsetp.gtu.or.f32 c, %19, %34, c;\nsetp.gtu.or.f32 d, %20, %34, d;\n"
        "setp.gtu.or.f32 a, %21, %33, a;\nsetp.gtu.or.f32 b, %22, %33, b;\nsetp.gtu.or.f32 c, %23, %34, c;\nsetp.gtu.or.f32 d, %24, %34, d;\n"
        "setp.gtu.or.f32 a, %25, %33, a;\nsetp.gtu.or.f32 b, %26, %33, b;\nsetp.gtu.or.f32 c, %27, %34, c;\nsetp.gtu.or.f32 d, %28, %34, d;\n"
        "setp.gtu.or.f32 a, %29, %33, a;\nsetp.gtu.or.f32 b, %30, %33, b;\nsetp.gtu.or.f32 c, %31, %34, c;\nsetp.gtu.or.f32 d, %32, %34, d;\n"
        "or.pred a, a, b;\nor.pred c, c, d;\nor.pred a, a, c;\nselp.u32 %0, 1, 0, a;\n}\n"
        : "=r"(r)
        :
        "f"(s[32]), "f"(s[33]), "f"(s[34]), "f"(s[35]), "f"(s[36]), "f"(s[37]), "f"(s[38]), "f"(s[39]),
        "f"(s[40]), "f"(s[41]), "f"(s[42]), "f"(s[43]), "f"(s[44]), "f"(s[45]), "f"(s[46]), "f"(s[47]),
        "f"(s[48]), "f"(s[49]), "f"(s[50]), "f"(s[51]), "f"(s[52]), "f"(s[53]), "f"(s[54]), "f"(s[55]),
        "f"(s[56]), "f"(s[57]), "f"(s[58]), "f"(s[59]), "f"(s[60]), "f"(s[61]), "f"(s[62]), "f"(s[63]),
        "f"(t0), "f"(t1));
    return r != 0;
}

__device__ __forceinline__ uint32_t desc_lo(uint32_t addr, uint32_t lbo_bytes) {
    return ((addr & 0x3FFFF) >> 4) | ((lbo_bytes >> 4) << 16);
}
__device__ __forceinline__ uint64_t desc64(uint32_t lo) {
    uint64_t d;
    asm("mov.b64 %0, {%1, %2};" : "=l"(d) : "r"(lo), "r"(0x40000040u));
    return d;
}

__device__ __forceinline__ void wgmma_ss_n128(float (&d)[64], uint64_t desc_a, uint64_t desc_b, int accumulate) {
    asm volatile(
        "{\n.reg .pred p;\nsetp.ne.b32 p, %66, 0;\n"
        "wgmma.mma_async.sync.aligned.m64n128k16.f32.bf16.bf16 {"
        "%0, %1, %2, %3, %4, %5, %6, %7, %8, %9, %10, %11, %12, %13, %14, %15, "
        "%16, %17, %18, %19, %20, %21, %22, %23, %24, %25, %26, %27, %28, %29, %30, %31, "
        "%32, %33, %34, %35, %36, %37, %38, %39, %40, %41, %42, %43, %44, %45, %46, %47, "
        "%48, %49, %50, %51, %52, %53, %54, %55, %56, %57, %58, %59, %60, %61, %62, %63"
        "}, %64, %65, p, 1, 1, 0, 0;\n}\n"
        :
        "+f"(d[0]), "+f"(d[1]), "+f"(d[2]), "+f"(d[3]), "+f"(d[4]), "+f"(d[5]), "+f"(d[6]), "+f"(d[7]),
        "+f"(d[8]), "+f"(d[9]), "+f"(d[10]), "+f"(d[11]), "+f"(d[12]), "+f"(d[13]), "+f"(d[14]), "+f"(d[15]),
        "+f"(d[16]), "+f"(d[17]), "+f"(d[18]), "+f"(d[19]), "+f"(d[20]), "+f"(d[21]), "+f"(d[22]), "+f"(d[23]),
        "+f"(d[24]), "+f"(d[25]), "+f"(d[26]), "+f"(d[27]), "+f"(d[28]), "+f"(d[29]), "+f"(d[30]), "+f"(d[31]),
        "+f"(d[32]), "+f"(d[33]), "+f"(d[34]), "+f"(d[35]), "+f"(d[36]), "+f"(d[37]), "+f"(d[38]), "+f"(d[39]),
        "+f"(d[40]), "+f"(d[41]), "+f"(d[42]), "+f"(d[43]), "+f"(d[44]), "+f"(d[45]), "+f"(d[46]), "+f"(d[47]),
        "+f"(d[48]), "+f"(d[49]), "+f"(d[50]), "+f"(d[51]), "+f"(d[52]), "+f"(d[53]), "+f"(d[54]), "+f"(d[55]),
        "+f"(d[56]), "+f"(d[57]), "+f"(d[58]), "+f"(d[59]), "+f"(d[60]), "+f"(d[61]), "+f"(d[62]), "+f"(d[63])
        : "l"(desc_a), "l"(desc_b), "r"(accumulate));
}

__device__ __forceinline__ void wgmma_rs_n256(float (&d)[128], uint32_t a0, uint32_t a1, uint32_t a2, uint32_t a3,
                                              uint64_t desc_b, int accumulate) {
    asm volatile(
        "{\n.reg .pred p;\nsetp.ne.b32 p, %133, 0;\n"
        "wgmma.mma_async.sync.aligned.m64n256k16.f32.bf16.bf16 {"
        "%0, %1, %2, %3, %4, %5, %6, %7, %8, %9, %10, %11, %12, %13, %14, %15, "
        "%16, %17, %18, %19, %20, %21, %22, %23, %24, %25, %26, %27, %28, %29, %30, %31, "
        "%32, %33, %34, %35, %36, %37, %38, %39, %40, %41, %42, %43, %44, %45, %46, %47, "
        "%48, %49, %50, %51, %52, %53, %54, %55, %56, %57, %58, %59, %60, %61, %62, %63, "
        "%64, %65, %66, %67, %68, %69, %70, %71, %72, %73, %74, %75, %76, %77, %78, %79, "
        "%80, %81, %82, %83, %84, %85, %86, %87, %88, %89, %90, %91, %92, %93, %94, %95, "
        "%96, %97, %98, %99, %100, %101, %102, %103, %104, %105, %106, %107, %108, %109, %110, %111, "
        "%112, %113, %114, %115, %116, %117, %118, %119, %120, %121, %122, %123, %124, %125, %126, %127"
        "}, {%128, %129, %130, %131}, %132, p, 1, 1, 1;\n}\n"
        :
        "+f"(d[0]), "+f"(d[1]), "+f"(d[2]), "+f"(d[3]), "+f"(d[4]), "+f"(d[5]), "+f"(d[6]), "+f"(d[7]),
        "+f"(d[8]), "+f"(d[9]), "+f"(d[10]), "+f"(d[11]), "+f"(d[12]), "+f"(d[13]), "+f"(d[14]), "+f"(d[15]),
        "+f"(d[16]), "+f"(d[17]), "+f"(d[18]), "+f"(d[19]), "+f"(d[20]), "+f"(d[21]), "+f"(d[22]), "+f"(d[23]),
        "+f"(d[24]), "+f"(d[25]), "+f"(d[26]), "+f"(d[27]), "+f"(d[28]), "+f"(d[29]), "+f"(d[30]), "+f"(d[31]),
        "+f"(d[32]), "+f"(d[33]), "+f"(d[34]), "+f"(d[35]), "+f"(d[36]), "+f"(d[37]), "+f"(d[38]), "+f"(d[39]),
        "+f"(d[40]), "+f"(d[41]), "+f"(d[42]), "+f"(d[43]), "+f"(d[44]), "+f"(d[45]), "+f"(d[46]), "+f"(d[47]),
        "+f"(d[48]), "+f"(d[49]), "+f"(d[50]), "+f"(d[51]), "+f"(d[52]), "+f"(d[53]), "+f"(d[54]), "+f"(d[55]),
        "+f"(d[56]), "+f"(d[57]), "+f"(d[58]), "+f"(d[59]), "+f"(d[60]), "+f"(d[61]), "+f"(d[62]), "+f"(d[63]),
        "+f"(d[64]), "+f"(d[65]), "+f"(d[66]), "+f"(d[67]), "+f"(d[68]), "+f"(d[69]), "+f"(d[70]), "+f"(d[71]),
        "+f"(d[72]), "+f"(d[73]), "+f"(d[74]), "+f"(d[75]), "+f"(d[76]), "+f"(d[77]), "+f"(d[78]), "+f"(d[79]),
        "+f"(d[80]), "+f"(d[81]), "+f"(d[82]), "+f"(d[83]), "+f"(d[84]), "+f"(d[85]), "+f"(d[86]), "+f"(d[87]),
        "+f"(d[88]), "+f"(d[89]), "+f"(d[90]), "+f"(d[91]), "+f"(d[92]), "+f"(d[93]), "+f"(d[94]), "+f"(d[95]),
        "+f"(d[96]), "+f"(d[97]), "+f"(d[98]), "+f"(d[99]), "+f"(d[100]), "+f"(d[101]), "+f"(d[102]), "+f"(d[103]),
        "+f"(d[104]), "+f"(d[105]), "+f"(d[106]), "+f"(d[107]), "+f"(d[108]), "+f"(d[109]), "+f"(d[110]), "+f"(d[111]),
        "+f"(d[112]), "+f"(d[113]), "+f"(d[114]), "+f"(d[115]), "+f"(d[116]), "+f"(d[117]), "+f"(d[118]), "+f"(d[119]),
        "+f"(d[120]), "+f"(d[121]), "+f"(d[122]), "+f"(d[123]), "+f"(d[124]), "+f"(d[125]), "+f"(d[126]), "+f"(d[127])
        : "r"(a0), "r"(a1), "r"(a2), "r"(a3), "l"(desc_b), "r"(accumulate));
}

__device__ __forceinline__ void wgmma_rs_n256_x4(float (&d)[128], const uint32_t* a, uint32_t desc_lo, int accumulate,
                                                 int again) {
    asm volatile(
        "{\n.reg .pred p, q, t;\n.reg .b32 lo;\n.reg .b64 d0, d1, d2, d3;\n"
        "setp.ne.b32 p, %145, 0;\nsetp.ne.b32 q, %146, 0;\nsetp.eq.b32 t, 0, 0;\n"
        "mov.b64 d0, {%144, 0x40000040};\n"
        "add.u32 lo, %144, 128;\nmov.b64 d1, {lo, 0x40000040};\n"
        "add.u32 lo, %144, 256;\nmov.b64 d2, {lo, 0x40000040};\n"
        "add.u32 lo, %144, 384;\nmov.b64 d3, {lo, 0x40000040};\n"
        "GROUP:\n"
        "wgmma.fence.sync.aligned;\n"
        "wgmma.mma_async.sync.aligned.m64n256k16.f32.bf16.bf16 {"
        "%0, %1, %2, %3, %4, %5, %6, %7, %8, %9, %10, %11, %12, %13, %14, %15, "
        "%16, %17, %18, %19, %20, %21, %22, %23, %24, %25, %26, %27, %28, %29, %30, %31, "
        "%32, %33, %34, %35, %36, %37, %38, %39, %40, %41, %42, %43, %44, %45, %46, %47, "
        "%48, %49, %50, %51, %52, %53, %54, %55, %56, %57, %58, %59, %60, %61, %62, %63, "
        "%64, %65, %66, %67, %68, %69, %70, %71, %72, %73, %74, %75, %76, %77, %78, %79, "
        "%80, %81, %82, %83, %84, %85, %86, %87, %88, %89, %90, %91, %92, %93, %94, %95, "
        "%96, %97, %98, %99, %100, %101, %102, %103, %104, %105, %106, %107, %108, %109, %110, %111, "
        "%112, %113, %114, %115, %116, %117, %118, %119, %120, %121, %122, %123, %124, %125, %126, %127"
        "}, {%636, %637, %638, %639}, d127, t, 1, 1, 1;\n"
        "wgmma.mma_async.sync.aligned.m64n256k16.f32.bf16.bf16 {"
        "%0, %1, %2, %3, %4, %5, %6, %7, %8, %9, %10, %11, %12, %13, %14, %15, "
        "%16, %17, %18, %19, %20, %21, %22, %23, %24, %25, %26, %27, %28, %29, %30, %31, "
        "%32, %33, %34, %35, %36, %37, %38, %39, %40, %41, %42, %43, %44, %45, %46, %47, "
        "%48, %49, %50, %51, %52, %53, %54, %55, %56, %57, %58, %59, %60, %61, %62, %63, "
        "%64, %65, %66, %67, %68, %69, %70, %71, %72, %73, %74, %75, %76, %77, %78, %79, "
        "%80, %81, %82, %83, %84, %85, %86, %87, %88, %89, %90, %91, %92, %93, %94, %95, "
        "%96, %97, %98, %99, %100, %101, %102, %103, %104, %105, %106, %107, %108, %109, %110, %111, "
        "%112, %113, %114, %115, %116, %117, %118, %119, %120, %121, %122, %123, %124, %125, %126, %127"
        "}, {%636, %637, %638, %639}, d127, t, 1, 1, 1;\n"
        "wgmma.mma_async.sync.aligned.m64n256k16.f32.bf16.bf16 {"
        "%0, %1, %2, %3, %4, %5, %6, %7, %8, %9, %10, %11, %12, %13, %14, %15, "
        "%16, %17, %18, %19, %20, %21, %22, %23, %24, %25, %26, %27, %28, %29, %30, %31, "
        "%32, %33, %34, %35, %36, %37, %38, %39, %40, %41, %42, %43, %44, %45, %46, %47, "
        "%48, %49, %50, %51, %52, %53, %54, %55, %56, %57, %58, %59, %60, %61, %62, %63, "
        "%64, %65, %66, %67, %68, %69, %70, %71, %72, %73, %74, %75, %76, %77, %78, %79, "
        "%80, %81, %82, %83, %84, %85, %86, %87, %88, %89, %90, %91, %92, %93, %94, %95, "
        "%96, %97, %98, %99, %100, %101, %102, %103, %104, %105, %106, %107, %108, %109, %110, %111, "
        "%112, %113, %114, %115, %116, %117, %118, %119, %120, %121, %122, %123, %124, %125, %126, %127"
        "}, {%636, %637, %638, %639}, d127, t, 1, 1, 1;\n"
        "wgmma.mma_async.sync.aligned.m64n256k16.f32.bf16.bf16 {"
        "%0, %1, %2, %3, %4, %5, %6, %7, %8, %9, %10, %11, %12, %13, %14, %15, "
        "%16, %17, %18, %19, %20, %21, %22, %23, %24, %25, %26, %27, %28, %29, %30, %31, "
        "%32, %33, %34, %35, %36, %37, %38, %39, %40, %41, %42, %43, %44, %45, %46, %47, "
        "%48, %49, %50, %51, %52, %53, %54, %55, %56, %57, %58, %59, %60, %61, %62, %63, "
        "%64, %65, %66, %67, %68, %69, %70, %71, %72, %73, %74, %75, %76, %77, %78, %79, "
        "%80, %81, %82, %83, %84, %85, %86, %87, %88, %89, %90, %91, %92, %93, %94, %95, "
        "%96, %97, %98, %99, %100, %101, %102, %103, %104, %105, %106, %107, %108, %109, %110, %111, "
        "%112, %113, %114, %115, %116, %117, %118, %119, %120, %121, %122, %123, %124, %125, %126, %127"
        "}, {%636, %637, %638, %639}, d127, t, 1, 1, 1;\n"
        "wgmma.commit_group.sync.aligned;\n"
        "@q bra GROUP;\n}\n"
        :
        "+f"(d[0]), "+f"(d[1]), "+f"(d[2]), "+f"(d[3]), "+f"(d[4]), "+f"(d[5]), "+f"(d[6]), "+f"(d[7]),
        "+f"(d[8]), "+f"(d[9]), "+f"(d[10]), "+f"(d[11]), "+f"(d[12]), "+f"(d[13]), "+f"(d[14]), "+f"(d[15]),
        "+f"(d[16]), "+f"(d[17]), "+f"(d[18]), "+f"(d[19]), "+f"(d[20]), "+f"(d[21]), "+f"(d[22]), "+f"(d[23]),
        "+f"(d[24]), "+f"(d[25]), "+f"(d[26]), "+f"(d[27]), "+f"(d[28]), "+f"(d[29]), "+f"(d[30]), "+f"(d[31]),
        "+f"(d[32]), "+f"(d[33]), "+f"(d[34]), "+f"(d[35]), "+f"(d[36]), "+f"(d[37]), "+f"(d[38]), "+f"(d[39]),
        "+f"(d[40]), "+f"(d[41]), "+f"(d[42]), "+f"(d[43]), "+f"(d[44]), "+f"(d[45]), "+f"(d[46]), "+f"(d[47]),
        "+f"(d[48]), "+f"(d[49]), "+f"(d[50]), "+f"(d[51]), "+f"(d[52]), "+f"(d[53]), "+f"(d[54]), "+f"(d[55]),
        "+f"(d[56]), "+f"(d[57]), "+f"(d[58]), "+f"(d[59]), "+f"(d[60]), "+f"(d[61]), "+f"(d[62]), "+f"(d[63]),
        "+f"(d[64]), "+f"(d[65]), "+f"(d[66]), "+f"(d[67]), "+f"(d[68]), "+f"(d[69]), "+f"(d[70]), "+f"(d[71]),
        "+f"(d[72]), "+f"(d[73]), "+f"(d[74]), "+f"(d[75]), "+f"(d[76]), "+f"(d[77]), "+f"(d[78]), "+f"(d[79]),
        "+f"(d[80]), "+f"(d[81]), "+f"(d[82]), "+f"(d[83]), "+f"(d[84]), "+f"(d[85]), "+f"(d[86]), "+f"(d[87]),
        "+f"(d[88]), "+f"(d[89]), "+f"(d[90]), "+f"(d[91]), "+f"(d[92]), "+f"(d[93]), "+f"(d[94]), "+f"(d[95]),
        "+f"(d[96]), "+f"(d[97]), "+f"(d[98]), "+f"(d[99]), "+f"(d[100]), "+f"(d[101]), "+f"(d[102]), "+f"(d[103]),
        "+f"(d[104]), "+f"(d[105]), "+f"(d[106]), "+f"(d[107]), "+f"(d[108]), "+f"(d[109]), "+f"(d[110]), "+f"(d[111]),
        "+f"(d[112]), "+f"(d[113]), "+f"(d[114]), "+f"(d[115]), "+f"(d[116]), "+f"(d[117]), "+f"(d[118]), "+f"(d[119]),
        "+f"(d[120]), "+f"(d[121]), "+f"(d[122]), "+f"(d[123]), "+f"(d[124]), "+f"(d[125]), "+f"(d[126]), "+f"(d[127])
        :
        "r"(a[0]), "r"(a[1]), "r"(a[2]), "r"(a[3]), "r"(a[4]), "r"(a[5]), "r"(a[6]), "r"(a[7]),
        "r"(a[8]), "r"(a[9]), "r"(a[10]), "r"(a[11]), "r"(a[12]), "r"(a[13]), "r"(a[14]), "r"(a[15]),
        "r"(desc_lo), "r"(accumulate), "r"(again)
        : "memory");
}

__device__ __forceinline__ void wgmma_pv_first6(float (&d)[128], const uint32_t* a, uint32_t desc0, uint32_t desc1, int accumulate, int again) {
    asm volatile(
        "{\n.reg .pred p, q, t;\n.reg .b32 lo;\n.reg .b64 d0, d1, d2, d3, d4, d5;\n"
        "setp.ne.b32 p, %154, 0;\nsetp.ne.b32 q, %155, 0;\nsetp.eq.b32 t, 0, 0;\n"
        "add.u32 lo, %152, 0;\nmov.b64 d0, {lo, 0x40000040};\n"
        "add.u32 lo, %152, 128;\nmov.b64 d1, {lo, 0x40000040};\n"
        "add.u32 lo, %152, 256;\nmov.b64 d2, {lo, 0x40000040};\n"
        "add.u32 lo, %152, 384;\nmov.b64 d3, {lo, 0x40000040};\n"
        "add.u32 lo, %153, 0;\nmov.b64 d4, {lo, 0x40000040};\n"
        "add.u32 lo, %153, 128;\nmov.b64 d5, {lo, 0x40000040};\n"
        "GROUP:\n"
        "wgmma.fence.sync.aligned;\n"
        "wgmma.mma_async.sync.aligned.m64n256k16.f32.bf16.bf16 {"
        "%0, %1, %2, %3, %4, %5, %6, %7, %8, %9, %10, %11, %12, %13, %14, %15, "
        "%16, %17, %18, %19, %20, %21, %22, %23, %24, %25, %26, %27, %28, %29, %30, %31, "
        "%32, %33, %34, %35, %36, %37, %38, %39, %40, %41, %42, %43, %44, %45, %46, %47, "
        "%48, %49, %50, %51, %52, %53, %54, %55, %56, %57, %58, %59, %60, %61, %62, %63, "
        "%64, %65, %66, %67, %68, %69, %70, %71, %72, %73, %74, %75, %76, %77, %78, %79, "
        "%80, %81, %82, %83, %84, %85, %86, %87, %88, %89, %90, %91, %92, %93, %94, %95, "
        "%96, %97, %98, %99, %100, %101, %102, %103, %104, %105, %106, %107, %108, %109, %110, %111, "
        "%112, %113, %114, %115, %116, %117, %118, %119, %120, %121, %122, %123, %124, %125, %126, %127"
        "}, {%636, %637, %638, %639}, d127, t, 1, 1, 1;\n"
        "wgmma.mma_async.sync.aligned.m64n256k16.f32.bf16.bf16 {"
        "%0, %1, %2, %3, %4, %5, %6, %7, %8, %9, %10, %11, %12, %13, %14, %15, "
        "%16, %17, %18, %19, %20, %21, %22, %23, %24, %25, %26, %27, %28, %29, %30, %31, "
        "%32, %33, %34, %35, %36, %37, %38, %39, %40, %41, %42, %43, %44, %45, %46, %47, "
        "%48, %49, %50, %51, %52, %53, %54, %55, %56, %57, %58, %59, %60, %61, %62, %63, "
        "%64, %65, %66, %67, %68, %69, %70, %71, %72, %73, %74, %75, %76, %77, %78, %79, "
        "%80, %81, %82, %83, %84, %85, %86, %87, %88, %89, %90, %91, %92, %93, %94, %95, "
        "%96, %97, %98, %99, %100, %101, %102, %103, %104, %105, %106, %107, %108, %109, %110, %111, "
        "%112, %113, %114, %115, %116, %117, %118, %119, %120, %121, %122, %123, %124, %125, %126, %127"
        "}, {%636, %637, %638, %639}, d127, t, 1, 1, 1;\n"
        "wgmma.mma_async.sync.aligned.m64n256k16.f32.bf16.bf16 {"
        "%0, %1, %2, %3, %4, %5, %6, %7, %8, %9, %10, %11, %12, %13, %14, %15, "
        "%16, %17, %18, %19, %20, %21, %22, %23, %24, %25, %26, %27, %28, %29, %30, %31, "
        "%32, %33, %34, %35, %36, %37, %38, %39, %40, %41, %42, %43, %44, %45, %46, %47, "
        "%48, %49, %50, %51, %52, %53, %54, %55, %56, %57, %58, %59, %60, %61, %62, %63, "
        "%64, %65, %66, %67, %68, %69, %70, %71, %72, %73, %74, %75, %76, %77, %78, %79, "
        "%80, %81, %82, %83, %84, %85, %86, %87, %88, %89, %90, %91, %92, %93, %94, %95, "
        "%96, %97, %98, %99, %100, %101, %102, %103, %104, %105, %106, %107, %108, %109, %110, %111, "
        "%112, %113, %114, %115, %116, %117, %118, %119, %120, %121, %122, %123, %124, %125, %126, %127"
        "}, {%636, %637, %638, %639}, d127, t, 1, 1, 1;\n"
        "wgmma.mma_async.sync.aligned.m64n256k16.f32.bf16.bf16 {"
        "%0, %1, %2, %3, %4, %5, %6, %7, %8, %9, %10, %11, %12, %13, %14, %15, "
        "%16, %17, %18, %19, %20, %21, %22, %23, %24, %25, %26, %27, %28, %29, %30, %31, "
        "%32, %33, %34, %35, %36, %37, %38, %39, %40, %41, %42, %43, %44, %45, %46, %47, "
        "%48, %49, %50, %51, %52, %53, %54, %55, %56, %57, %58, %59, %60, %61, %62, %63, "
        "%64, %65, %66, %67, %68, %69, %70, %71, %72, %73, %74, %75, %76, %77, %78, %79, "
        "%80, %81, %82, %83, %84, %85, %86, %87, %88, %89, %90, %91, %92, %93, %94, %95, "
        "%96, %97, %98, %99, %100, %101, %102, %103, %104, %105, %106, %107, %108, %109, %110, %111, "
        "%112, %113, %114, %115, %116, %117, %118, %119, %120, %121, %122, %123, %124, %125, %126, %127"
        "}, {%636, %637, %638, %639}, d127, t, 1, 1, 1;\n"
        "wgmma.commit_group.sync.aligned;\n"
        "wgmma.mma_async.sync.aligned.m64n256k16.f32.bf16.bf16 {"
        "%0, %1, %2, %3, %4, %5, %6, %7, %8, %9, %10, %11, %12, %13, %14, %15, "
        "%16, %17, %18, %19, %20, %21, %22, %23, %24, %25, %26, %27, %28, %29, %30, %31, "
        "%32, %33, %34, %35, %36, %37, %38, %39, %40, %41, %42, %43, %44, %45, %46, %47, "
        "%48, %49, %50, %51, %52, %53, %54, %55, %56, %57, %58, %59, %60, %61, %62, %63, "
        "%64, %65, %66, %67, %68, %69, %70, %71, %72, %73, %74, %75, %76, %77, %78, %79, "
        "%80, %81, %82, %83, %84, %85, %86, %87, %88, %89, %90, %91, %92, %93, %94, %95, "
        "%96, %97, %98, %99, %100, %101, %102, %103, %104, %105, %106, %107, %108, %109, %110, %111, "
        "%112, %113, %114, %115, %116, %117, %118, %119, %120, %121, %122, %123, %124, %125, %126, %127"
        "}, {%636, %637, %638, %639}, d127, t, 1, 1, 1;\n"
        "wgmma.mma_async.sync.aligned.m64n256k16.f32.bf16.bf16 {"
        "%0, %1, %2, %3, %4, %5, %6, %7, %8, %9, %10, %11, %12, %13, %14, %15, "
        "%16, %17, %18, %19, %20, %21, %22, %23, %24, %25, %26, %27, %28, %29, %30, %31, "
        "%32, %33, %34, %35, %36, %37, %38, %39, %40, %41, %42, %43, %44, %45, %46, %47, "
        "%48, %49, %50, %51, %52, %53, %54, %55, %56, %57, %58, %59, %60, %61, %62, %63, "
        "%64, %65, %66, %67, %68, %69, %70, %71, %72, %73, %74, %75, %76, %77, %78, %79, "
        "%80, %81, %82, %83, %84, %85, %86, %87, %88, %89, %90, %91, %92, %93, %94, %95, "
        "%96, %97, %98, %99, %100, %101, %102, %103, %104, %105, %106, %107, %108, %109, %110, %111, "
        "%112, %113, %114, %115, %116, %117, %118, %119, %120, %121, %122, %123, %124, %125, %126, %127"
        "}, {%636, %637, %638, %639}, d127, t, 1, 1, 1;\n"
        "wgmma.commit_group.sync.aligned;\n"
        "@q bra GROUP;\n}\n"
        :
        "+f"(d[0]), "+f"(d[1]), "+f"(d[2]), "+f"(d[3]), "+f"(d[4]), "+f"(d[5]), "+f"(d[6]), "+f"(d[7]),
        "+f"(d[8]), "+f"(d[9]), "+f"(d[10]), "+f"(d[11]), "+f"(d[12]), "+f"(d[13]), "+f"(d[14]), "+f"(d[15]),
        "+f"(d[16]), "+f"(d[17]), "+f"(d[18]), "+f"(d[19]), "+f"(d[20]), "+f"(d[21]), "+f"(d[22]), "+f"(d[23]),
        "+f"(d[24]), "+f"(d[25]), "+f"(d[26]), "+f"(d[27]), "+f"(d[28]), "+f"(d[29]), "+f"(d[30]), "+f"(d[31]),
        "+f"(d[32]), "+f"(d[33]), "+f"(d[34]), "+f"(d[35]), "+f"(d[36]), "+f"(d[37]), "+f"(d[38]), "+f"(d[39]),
        "+f"(d[40]), "+f"(d[41]), "+f"(d[42]), "+f"(d[43]), "+f"(d[44]), "+f"(d[45]), "+f"(d[46]), "+f"(d[47]),
        "+f"(d[48]), "+f"(d[49]), "+f"(d[50]), "+f"(d[51]), "+f"(d[52]), "+f"(d[53]), "+f"(d[54]), "+f"(d[55]),
        "+f"(d[56]), "+f"(d[57]), "+f"(d[58]), "+f"(d[59]), "+f"(d[60]), "+f"(d[61]), "+f"(d[62]), "+f"(d[63]),
        "+f"(d[64]), "+f"(d[65]), "+f"(d[66]), "+f"(d[67]), "+f"(d[68]), "+f"(d[69]), "+f"(d[70]), "+f"(d[71]),
        "+f"(d[72]), "+f"(d[73]), "+f"(d[74]), "+f"(d[75]), "+f"(d[76]), "+f"(d[77]), "+f"(d[78]), "+f"(d[79]),
        "+f"(d[80]), "+f"(d[81]), "+f"(d[82]), "+f"(d[83]), "+f"(d[84]), "+f"(d[85]), "+f"(d[86]), "+f"(d[87]),
        "+f"(d[88]), "+f"(d[89]), "+f"(d[90]), "+f"(d[91]), "+f"(d[92]), "+f"(d[93]), "+f"(d[94]), "+f"(d[95]),
        "+f"(d[96]), "+f"(d[97]), "+f"(d[98]), "+f"(d[99]), "+f"(d[100]), "+f"(d[101]), "+f"(d[102]), "+f"(d[103]),
        "+f"(d[104]), "+f"(d[105]), "+f"(d[106]), "+f"(d[107]), "+f"(d[108]), "+f"(d[109]), "+f"(d[110]), "+f"(d[111]),
        "+f"(d[112]), "+f"(d[113]), "+f"(d[114]), "+f"(d[115]), "+f"(d[116]), "+f"(d[117]), "+f"(d[118]), "+f"(d[119]),
        "+f"(d[120]), "+f"(d[121]), "+f"(d[122]), "+f"(d[123]), "+f"(d[124]), "+f"(d[125]), "+f"(d[126]), "+f"(d[127])
        :
        "r"(a[0]), "r"(a[1]), "r"(a[2]), "r"(a[3]), "r"(a[4]), "r"(a[5]), "r"(a[6]), "r"(a[7]),
        "r"(a[8]), "r"(a[9]), "r"(a[10]), "r"(a[11]), "r"(a[12]), "r"(a[13]), "r"(a[14]), "r"(a[15]),
        "r"(a[16]), "r"(a[17]), "r"(a[18]), "r"(a[19]), "r"(a[20]), "r"(a[21]), "r"(a[22]), "r"(a[23]),
        "r"(desc0), "r"(desc1), "r"(accumulate), "r"(again)
        : "memory");
}

__device__ __forceinline__ void wgmma_pv_last2(float (&d)[128], const uint32_t* a, uint32_t desc0, int accumulate, int again) {
    asm volatile(
        "{\n.reg .pred p, q, t;\n.reg .b32 lo;\n.reg .b64 d0, d1;\n"
        "setp.ne.b32 p, %137, 0;\nsetp.ne.b32 q, %138, 0;\nsetp.eq.b32 t, 0, 0;\n"
        "add.u32 lo, %136, 256;\nmov.b64 d0, {lo, 0x40000040};\n"
        "add.u32 lo, %136, 384;\nmov.b64 d1, {lo, 0x40000040};\n"
        "GROUP:\n"
        "wgmma.fence.sync.aligned;\n"
        "wgmma.mma_async.sync.aligned.m64n256k16.f32.bf16.bf16 {"
        "%0, %1, %2, %3, %4, %5, %6, %7, %8, %9, %10, %11, %12, %13, %14, %15, "
        "%16, %17, %18, %19, %20, %21, %22, %23, %24, %25, %26, %27, %28, %29, %30, %31, "
        "%32, %33, %34, %35, %36, %37, %38, %39, %40, %41, %42, %43, %44, %45, %46, %47, "
        "%48, %49, %50, %51, %52, %53, %54, %55, %56, %57, %58, %59, %60, %61, %62, %63, "
        "%64, %65, %66, %67, %68, %69, %70, %71, %72, %73, %74, %75, %76, %77, %78, %79, "
        "%80, %81, %82, %83, %84, %85, %86, %87, %88, %89, %90, %91, %92, %93, %94, %95, "
        "%96, %97, %98, %99, %100, %101, %102, %103, %104, %105, %106, %107, %108, %109, %110, %111, "
        "%112, %113, %114, %115, %116, %117, %118, %119, %120, %121, %122, %123, %124, %125, %126, %127"
        "}, {%636, %637, %638, %639}, d127, t, 1, 1, 1;\n"
        "wgmma.mma_async.sync.aligned.m64n256k16.f32.bf16.bf16 {"
        "%0, %1, %2, %3, %4, %5, %6, %7, %8, %9, %10, %11, %12, %13, %14, %15, "
        "%16, %17, %18, %19, %20, %21, %22, %23, %24, %25, %26, %27, %28, %29, %30, %31, "
        "%32, %33, %34, %35, %36, %37, %38, %39, %40, %41, %42, %43, %44, %45, %46, %47, "
        "%48, %49, %50, %51, %52, %53, %54, %55, %56, %57, %58, %59, %60, %61, %62, %63, "
        "%64, %65, %66, %67, %68, %69, %70, %71, %72, %73, %74, %75, %76, %77, %78, %79, "
        "%80, %81, %82, %83, %84, %85, %86, %87, %88, %89, %90, %91, %92, %93, %94, %95, "
        "%96, %97, %98, %99, %100, %101, %102, %103, %104, %105, %106, %107, %108, %109, %110, %111, "
        "%112, %113, %114, %115, %116, %117, %118, %119, %120, %121, %122, %123, %124, %125, %126, %127"
        "}, {%636, %637, %638, %639}, d127, t, 1, 1, 1;\n"
        "wgmma.commit_group.sync.aligned;\n"
        "@q bra GROUP;\n}\n"
        :
        "+f"(d[0]), "+f"(d[1]), "+f"(d[2]), "+f"(d[3]), "+f"(d[4]), "+f"(d[5]), "+f"(d[6]), "+f"(d[7]),
        "+f"(d[8]), "+f"(d[9]), "+f"(d[10]), "+f"(d[11]), "+f"(d[12]), "+f"(d[13]), "+f"(d[14]), "+f"(d[15]),
        "+f"(d[16]), "+f"(d[17]), "+f"(d[18]), "+f"(d[19]), "+f"(d[20]), "+f"(d[21]), "+f"(d[22]), "+f"(d[23]),
        "+f"(d[24]), "+f"(d[25]), "+f"(d[26]), "+f"(d[27]), "+f"(d[28]), "+f"(d[29]), "+f"(d[30]), "+f"(d[31]),
        "+f"(d[32]), "+f"(d[33]), "+f"(d[34]), "+f"(d[35]), "+f"(d[36]), "+f"(d[37]), "+f"(d[38]), "+f"(d[39]),
        "+f"(d[40]), "+f"(d[41]), "+f"(d[42]), "+f"(d[43]), "+f"(d[44]), "+f"(d[45]), "+f"(d[46]), "+f"(d[47]),
        "+f"(d[48]), "+f"(d[49]), "+f"(d[50]), "+f"(d[51]), "+f"(d[52]), "+f"(d[53]), "+f"(d[54]), "+f"(d[55]),
        "+f"(d[56]), "+f"(d[57]), "+f"(d[58]), "+f"(d[59]), "+f"(d[60]), "+f"(d[61]), "+f"(d[62]), "+f"(d[63]),
        "+f"(d[64]), "+f"(d[65]), "+f"(d[66]), "+f"(d[67]), "+f"(d[68]), "+f"(d[69]), "+f"(d[70]), "+f"(d[71]),
        "+f"(d[72]), "+f"(d[73]), "+f"(d[74]), "+f"(d[75]), "+f"(d[76]), "+f"(d[77]), "+f"(d[78]), "+f"(d[79]),
        "+f"(d[80]), "+f"(d[81]), "+f"(d[82]), "+f"(d[83]), "+f"(d[84]), "+f"(d[85]), "+f"(d[86]), "+f"(d[87]),
        "+f"(d[88]), "+f"(d[89]), "+f"(d[90]), "+f"(d[91]), "+f"(d[92]), "+f"(d[93]), "+f"(d[94]), "+f"(d[95]),
        "+f"(d[96]), "+f"(d[97]), "+f"(d[98]), "+f"(d[99]), "+f"(d[100]), "+f"(d[101]), "+f"(d[102]), "+f"(d[103]),
        "+f"(d[104]), "+f"(d[105]), "+f"(d[106]), "+f"(d[107]), "+f"(d[108]), "+f"(d[109]), "+f"(d[110]), "+f"(d[111]),
        "+f"(d[112]), "+f"(d[113]), "+f"(d[114]), "+f"(d[115]), "+f"(d[116]), "+f"(d[117]), "+f"(d[118]), "+f"(d[119]),
        "+f"(d[120]), "+f"(d[121]), "+f"(d[122]), "+f"(d[123]), "+f"(d[124]), "+f"(d[125]), "+f"(d[126]), "+f"(d[127])
        :
        "r"(a[0]), "r"(a[1]), "r"(a[2]), "r"(a[3]), "r"(a[4]), "r"(a[5]), "r"(a[6]), "r"(a[7]),
        "r"(desc0), "r"(accumulate), "r"(again)
        : "memory");
}

#define TR(role, idx)
#define TRG(role, idx)

constexpr int kSwapItem = kItemsPerTile + 2;
constexpr int kStageItem0 = STAGE_MODE == 1 ? 13 : 14;
__device__ __forceinline__ uint32_t slot_of(uint32_t pos, bool swapped) {
    return pos;
}
struct Ring {
    uint32_t pos, phase;
    __device__ __forceinline__ void advance() {
        if (++pos == kNumSlots) { pos = 0; phase ^= 1; }
    }
};

__device__ __forceinline__ int tile_of_cta(int block) {
    const int c = block >> 1;
    int group, sub;
    if (c < 4)       { group = 30 + ((c == 1 || c == 2) ? 1 : 0); sub = c >> 1; }
    else if (c < 36) { const int u = c - 4;  group = ((u >> 4) << 3) + (u & 7); sub = (u >> 3) & 1; }
    else             { const int u = c - 36; const int h = u >= 14, v = u - 14 * h; sub = v >= 7; group = 16 + 7 * h + v - 7 * sub; }
    return group * 4 + sub * 2 + (block & 1);
}

__global__ void __cluster_dims__(2, 1, 1) __launch_bounds__(384, 1)
gqa_fwd_kernel(const __grid_constant__ CUtensorMap map_q, const __grid_constant__ CUtensorMap map_k,
               const __grid_constant__ CUtensorMap map_v, const __grid_constant__ CUtensorMap map_o,
               const __grid_constant__ CUtensorMap map_o16,
               const uint8_t* __restrict__ gq, const uint8_t* __restrict__ gk, const uint8_t* __restrict__ gv) {
    extern __shared__ __align__(1024) uint8_t smem_raw[];
    const uint32_t smem = smem_u32(smem_raw);
    const uint32_t bars = smem + kSmemBar;
    const int tid = threadIdx.x;
    const int wg = __shfl_sync(0xffffffffu, tid >> 7, 0);
    const uint32_t cta_rank = blockIdx.x & 1;
    const int tile0 = tile_of_cta(blockIdx.x);

    const int group0 = tile0 >> 2;
    const bool late = (group0 < 16) ? (group0 >= 8) : (group0 < 30 ? group0 >= 23 : group0 == 31);
    const long long t_start = clock64();
    if (late && wg < 2) while (clock64() - t_start < STAGGER) {}
    if (wg == 0) l2_localize(gq + (size_t)tile0 * 65536 + tid * 256);
    if (wg == 1) l2_localize(gk + (size_t)(tile0 >> 2) * 262144 + cta_rank * 32768 + (tid & 127) * 256);
    if (tid == 256) {
        prefetch_map(&map_q);
        prefetch_map(&map_k);
        prefetch_map(&map_v);
        prefetch_map(&map_o);
        prefetch_map(&map_o16);
        for (int s = 0; s < kNumSlots; ++s) {
            mbar_init(bars + kBarFull + 8 * s, 1);
            mbar_init(bars + kBarEmpty + 8 * s, 4);
        }
        for (int w = 0; w < 2; ++w) {
            mbar_init(bars + kBarQFull + 16 * w, 1);
            mbar_init(bars + kBarQFull + 16 * w + 8, 1);
            mbar_init(bars + kBarQEmpty + 8 * w, 1);
            mbar_init(bars + kBarStageOk + 8 * w, 1);
            mbar_init(bars + kBarStaged + 8 * w, 4);
        }
        mbar_init(bars + kBarPrefetchGo, 1);
        mbar_init(bars + kBarPrefetchGo + 8, 1);
        asm volatile("fence.mbarrier_init.release.cluster;" ::: "memory");
    }
    __syncthreads();
    asm volatile("barrier.cluster.arrive.relaxed.aligned;" ::: "memory");

    if (wg == 2) {
        asm volatile("setmaxnreg.dec.sync.aligned.u32 24;");
        const int warp = (tid >> 5) & 3;
        if (warp == 0) {
            auto load_q = [&](int t, int w, int h) {
                const uint32_t bar = bars + kBarQFull + 16 * w + 8 * h;
                mbar_expect_tx(bar, 16384);
                tma_load(smem + kSmemQ + w * 32768 + h * 16384, &map_q, bar,
                         (t * kNumCtas + tile0) * 128 + w * 64, 2 * h);
            };
            auto load_kv = [&](int i, uint32_t slot) {
                const int t = i >> 4, j = (i >> 2) & 3, kind = i & 3;
                const int kv_row = (((t * kNumCtas + tile0) >> 2) << 9) + j * 128;
                const uint32_t full = bars + kBarFull + 8 * slot;
                const uint32_t dst = smem + kSmemRing + slot * kSlotBytes + cta_rank * 16384;
                TR(2, i);
                mbar_expect_tx(full, kSlotBytes);
                if (kind < 2) tma_load_mc(dst, &map_k, full, kv_row, kind * 2 + cta_rank);
                else          tma_load_mc(dst, &map_v, full, kv_row + (kind - 2) * 64, cta_rank * 2);
            };
            const bool leader = (tid & 31) == 0;
            if (late) while (clock64() - t_start < STAGGER) {}
            if (leader) load_q(0, 0, 0);
            __syncwarp();
            asm volatile("barrier.cluster.wait.aligned;" ::: "memory");
            if (leader) {
                auto start_bar = [&](int n) -> uint32_t {
                    if (n == 0) return bars + kBarQFull;
                    if (n == 2) return bars + kBarQFull + 8;
                    if (n == 4) return bars + kBarQFull + 16;
                    if (n == 5) return bars + kBarQFull + 24;
                    return bars + kBarFull + 8 * (n < 4 ? (n >> 1) : (n - 4));
                };
#pragma unroll
                for (int n = 1; n < 9; ++n) {
                    if (n >= START_WINDOW) mbar_wait(start_bar(n - START_WINDOW), 0);
                    if (n == 2) load_q(0, 0, 1);
                    else if (n == 4) load_q(0, 1, 0);
                    else if (n == 5) load_q(0, 1, 1);
                    else load_kv(n < 4 ? (n >> 1) : (n - 4), n < 4 ? (n >> 1) : (n - 4));
                }
                auto store_out = [&](int w) {
                    const uint32_t slot = (w == 0 ? kStageItem0 : 15) % kNumSlots;
                    mbar_wait(bars + kBarStaged + 8 * w, 0);
                    TR(3, 8 + w);
                    tma_store(&map_o, smem + kSmemRing + slot * kSlotBytes, tile0 * 128 + w * 64, 0);
                    asm volatile("cp.async.bulk.wait_group.read 0;" ::: "memory");
                    TR(3, w);
                    mbar_arrive_cta(bars + kBarEmpty + 8 * slot, 0);
                    mbar_arrive_cta(bars + kBarEmpty + 8 * slot, 1);
                };
                Ring r{0, 0};
#pragma unroll 1
                for (int i = kNumSlots; i < kNumItems; ++i) {
                    if (i == PF_Q0) mbar_arrive(bars + kBarPrefetchGo);
                    if (i == PF_KV2) mbar_arrive(bars + kBarPrefetchGo + 8);
                    if (i == kItemsPerTile + 1) { mbar_wait(bars + kBarQEmpty, 0); load_q(1, 0, 0); load_q(1, 0, 1); }
                    if (i == kItemsPerTile + 2) { mbar_wait(bars + kBarQEmpty + 8, 0); load_q(1, 1, 0); load_q(1, 1, 1); }
                    if (i == kItemsPerTile + 3) store_out(0);
                    if (i == kItemsPerTile + 4) store_out(1);
                    const uint32_t slot = slot_of(r.pos, i >= kSwapItem);
                    mbar_wait(bars + kBarEmpty + 8 * slot, r.phase);
                    load_kv(i, slot);
                    r.advance();
                }
            }
        } else {
            asm volatile("barrier.cluster.wait.aligned;" ::: "memory");
            if (warp == 1) {
                mbar_wait(bars + kBarPrefetchGo, 0);
#pragma unroll 1
                for (int i = 0; i < 8; ++i)
                    l2_localize(gq + (size_t)(kNumCtas + tile0) * 65536 + i * 8192 + (tid & 31) * 256);
                mbar_wait(bars + kBarPrefetchGo + 8, 0);
                {
                    const size_t off = (size_t)((kNumCtas + tile0) >> 2) * 262144 + (tile0 & 3) * 16384 + (tid & 31) * 256;
                    uint32_t u0, u1, u2, u3;
                    asm volatile("ld.volatile.global.L2::256B.b32 %0, [%1];" : "=r"(u0) : "l"(gv + off) : "memory");
                    asm volatile("ld.volatile.global.L2::256B.b32 %0, [%1];" : "=r"(u1) : "l"(gv + off + 8192) : "memory");
                    asm volatile("ld.volatile.global.L2::256B.b32 %0, [%1];" : "=r"(u2) : "l"(gk + off + 65536) : "memory");
                    asm volatile("ld.volatile.global.L2::256B.b32 %0, [%1];" : "=r"(u3) : "l"(gk + off + 65536 + 8192) : "memory");
                }
            }
        }
    } else {
        asm volatile("setmaxnreg.inc.sync.aligned.u32 240;");
        asm volatile("barrier.cluster.wait.aligned;" ::: "memory");
        const int lane = tid & 31;
        const int wtid = tid & 127;
        const int my_turn = kNamedTurn + wg, other_turn = kNamedTurn + (wg ^ 1);
        const uint32_t desc_q = desc_lo(smem + kSmemQ + wg * 32768, 16);
        const uint32_t desc_k0 = desc_lo(smem + kSmemRing, 16);
        const uint32_t desc_v0 = desc_lo(smem + kSmemRing, 8192);
        const int never = (int)(reinterpret_cast<uintptr_t>(gq) & 1);

        uint32_t empty_remote;
        asm("mapa.shared::cluster.u32 %0, %1, %2;" : "=r"(empty_remote) : "r"(bars + kBarEmpty), "r"(wtid & 1));
        auto release = [&](uint32_t slot) {
            if (wtid < 2)
                asm volatile("mbarrier.arrive.shared::cluster.b64 _, [%0];" ::"r"(empty_remote + 8 * slot) : "memory");
        };

        auto stage_first_tile = [&](const float (&o)[128]) {
            const uint32_t slot = wg == 0 ? kStageItem0 % kNumSlots : 15 % kNumSlots;
            const int row = ((wtid >> 5) << 4) + (lane & 7) + (((lane >> 3) & 1) << 3);
            const uint32_t base = smem + kSmemRing + slot * kSlotBytes + row * 128 + ((((lane >> 4) ^ lane) & 7) << 4);
            mbar_wait(bars + kBarStageOk + 8 * wg, 0);
#pragma unroll
            for (int i = 0; i < 32; i += 2) {
                const uint32_t addr = (base ^ ((i & 7) << 4)) + (i >> 3) * 8192;
                asm volatile("stmatrix.sync.aligned.m8n8.x4.shared.b16 [%0], {%1, %2, %3, %4};"
                             ::"r"(addr), "r"(__float_as_uint(o[2 * i])), "r"(__float_as_uint(o[2 * i + 1])),
                               "r"(__float_as_uint(o[2 * i + 2])), "r"(__float_as_uint(o[2 * i + 3])) : "memory");
            }
            asm volatile("fence.proxy.async.shared::cta;" ::: "memory");
            __syncwarp();
            if (lane == 0) mbar_arrive(bars + kBarStaged + 8 * wg);
        };

        if (wg == 1) named_arrive(kNamedTurn, 256);

        float o[128];
        float m0 = 0.f, m1 = 0.f, l0 = 0.f, l1 = 0.f, inv0 = 0.f, inv1 = 0.f;
        Ring r{0, 0};
#pragma unroll 1
        for (int it = 0; it < 4 * kTilesPerCta; ++it) {
            const int t = it >> 2, j = it & 3;
            const int item = it * 4;

            float s[64];
            const uint32_t ka = slot_of(r.pos, item >= kSwapItem), ka_ph = r.phase; r.advance();
            const uint32_t kb = slot_of(r.pos, item + 1 >= kSwapItem), kb_ph = r.phase; r.advance();
            const uint32_t va = slot_of(r.pos, item + 2 >= kSwapItem), va_ph = r.phase; r.advance();
            const uint32_t vb = slot_of(r.pos, item + 3 >= kSwapItem), vb_ph = r.phase; r.advance();

            if (j == 0) {
                m0 = m1 = -INFINITY;
                l0 = l1 = 0.f;
                mbar_wait(bars + kBarQFull + 16 * wg, t);
            }
            TR(wg, it * 12 + 0);
            mbar_wait(bars + kBarFull + 8 * ka, ka_ph);
            TR(wg, it * 12 + 1);
            named_sync(my_turn, 256);
            wgmma_fence();
            {
                const uint32_t dk = desc_k0 + ka * (kSlotBytes >> 4);
#pragma unroll
                for (int ks = 0; ks < 8; ++ks)
                    wgmma_ss_n128(s, desc64(desc_q + (ks >> 2) * (8192 >> 4) + (ks & 3) * 2),
                                  desc64(dk + (ks >> 2) * (16384 >> 4) + (ks & 3) * 2), ks != 0);
            }
            wgmma_commit();
            if (j == 0) mbar_wait(bars + kBarQFull + 16 * wg + 8, t);
            mbar_wait(bars + kBarFull + 8 * kb, kb_ph);
            {
                const uint32_t dk = desc_k0 + kb * (kSlotBytes >> 4);
#pragma unroll
                for (int ks = 0; ks < 8; ++ks)
                    wgmma_ss_n128(s, desc64(desc_q + (2 + (ks >> 2)) * (8192 >> 4) + (ks & 3) * 2),
                                  desc64(dk + (ks >> 2) * (16384 >> 4) + (ks & 3) * 2), 1);
            }
            wgmma_commit();
            named_arrive(other_turn, 256);
            TR(wg, it * 12 + 3);
            TR(wg, it * 12 + 2);
            wgmma_wait<1>();
            if (item + 0 + kNumSlots < kNumItems) release(ka);
            wgmma_wait<0>();
            if (STAGE_MODE == 1 && it == 3) {
                if (wg == 1) {
                    if (wtid == 0) mbar_arrive(bars + kBarStageOk);
                    release(kb);
                }
            } else if (item + 1 + kNumSlots < kNumItems) {
                release(kb);
            }
            if (j == 3 && t + 1 < kTilesPerCta && wtid == 0) mbar_arrive(bars + kBarQEmpty + 8 * wg);
            pin_regs(s);
            TR(wg, it * 12 + 4);

            uint32_t p[32];
            float t0, t1;
            auto exp_steps = [&](int k0, int k1, float b0, float b1) {
#pragma unroll
                for (int i = 2 * k0; i < 2 * k1; ++i) {
                    const float e0 = ex2(fmaf(s[4 * i], kScaleLog2, -b0));
                    const float e1 = ex2(fmaf(s[4 * i + 1], kScaleLog2, -b0));
                    const float e2 = ex2(fmaf(s[4 * i + 2], kScaleLog2, -b1));
                    const float e3 = ex2(fmaf(s[4 * i + 3], kScaleLog2, -b1));
                    t0 += e0 + e1;
                    t1 += e2 + e3;
                    p[2 * i] = pack_bf16(e0, e1);
                    p[2 * i + 1] = pack_bf16(e2, e3);
                }
            };
            bool moved = true;
            if (j != 0) moved = any_above(s, m0 + kLazyRaw, m1 + kLazyRaw);
            if (__any_sync(0xffffffffu, moved)) {
                float x0 = fmaxf(s[0], s[1]), x1 = fmaxf(s[2], s[3]);
                float y0 = fmaxf(s[4], s[5]), y1 = fmaxf(s[6], s[7]);
#pragma unroll
                for (int i = 2; i < 16; i += 2) {
                    x0 = fmaxf(x0, fmaxf(s[4 * i], s[4 * i + 1]));
                    x1 = fmaxf(x1, fmaxf(s[4 * i + 2], s[4 * i + 3]));
                    y0 = fmaxf(y0, fmaxf(s[4 * i + 4], s[4 * i + 5]));
                    y1 = fmaxf(y1, fmaxf(s[4 * i + 6], s[4 * i + 7]));
                }
                x0 = fmaxf(x0, y0);
                x1 = fmaxf(x1, y1);
                x0 = fmaxf(x0, __shfl_xor_sync(0xffffffffu, x0, 1));
                x1 = fmaxf(x1, __shfl_xor_sync(0xffffffffu, x1, 1));
                x0 = fmaxf(x0, __shfl_xor_sync(0xffffffffu, x0, 2));
                x1 = fmaxf(x1, __shfl_xor_sync(0xffffffffu, x1, 2));
                x0 = fmaxf(x0, m0);
                x1 = fmaxf(x1, m1);
                const float a0 = ex2((m0 - x0) * kScaleLog2), a1 = ex2((m1 - x1) * kScaleLog2);
                m0 = x0;
                m1 = x1;
                l0 *= a0;
                l1 *= a1;
                if (j != 0) {
#pragma unroll
                    for (int i = 0; i < 32; ++i) {
                        o[4 * i] *= a0;
                        o[4 * i + 1] *= a0;
                        o[4 * i + 2] *= a1;
                        o[4 * i + 3] *= a1;
                    }
                }
            }
            const float b0 = m0 * kScaleLog2, b1 = m1 * kScaleLog2;
            t0 = t1 = 0.f;
            exp_steps(0, SM_FIRST, b0, b1);

            TR(wg, it * 12 + 5);
            mbar_wait(bars + kBarFull + 8 * va, va_ph);
            TR(wg, it * 12 + 6);
            named_sync(my_turn, 256);
            wgmma_rs_n256_x4(o, p, desc_v0 + va * (kSlotBytes >> 4), j != 0, never);
            TR(wg, it * 12 + 7);
            exp_steps(SM_FIRST, 8, b0, b1);
            l0 += t0;
            l1 += t1;
            TR(wg, it * 12 + 8);
            mbar_wait(bars + kBarFull + 8 * vb, vb_ph);
            wgmma_rs_n256_x4(o, p + 16, desc_v0 + vb * (kSlotBytes >> 4), 1, never);
            if (wg == 0 || it + 1 < 4 * kTilesPerCta) named_arrive(other_turn, 256);
            TR(wg, it * 12 + 9);
            if (j == 3) {
                l0 += __shfl_xor_sync(0xffffffffu, l0, 1);
                l1 += __shfl_xor_sync(0xffffffffu, l1, 1);
                l0 += __shfl_xor_sync(0xffffffffu, l0, 2);
                l1 += __shfl_xor_sync(0xffffffffu, l1, 2);
                inv0 = rcp(l0);
                inv1 = rcp(l1);
            }

            wgmma_wait<PV_WAIT_FIRST>();
            if (STAGE_MODE == 0 && it == 3) {
                if (wg == 1) {
                    if (wtid == 0) mbar_arrive(bars + kBarStageOk);
                    release(va);
                }
            } else if (item + 2 + kNumSlots < kNumItems) {
                release(va);
            }
            wgmma_wait<0>();
            if (j == 3 && t == 0) {
                if (wg == 0) {
                    if (wtid == 0) mbar_arrive(bars + kBarStageOk + 8);
                    release(vb);
                }
            } else if (item + 3 + kNumSlots < kNumItems) {
                release(vb);
            }
            pin_regs(o);
            TR(wg, it * 12 + 10);

            if (j == 3 && t + 1 < kTilesPerCta) {
                {
#pragma unroll
                    for (int i = 0; i < 32; ++i) {
                        const uint32_t r0 = pack_bf16(o[4 * i] * inv0, o[4 * i + 1] * inv0);
                        const uint32_t r1 = pack_bf16(o[4 * i + 2] * inv1, o[4 * i + 3] * inv1);
                        o[2 * i] = __uint_as_float(r0);
                        o[2 * i + 1] = __uint_as_float(r1);
                    }
                    stage_first_tile(o);
                }
            }
            TR(wg, it * 12 + 11);
        }
        {
            const uint32_t stage = smem + kSmemQ + wg * 32768 + (wtid >> 5) * 8192;
            const int row = (lane & 7) + (((lane >> 3) & 1) << 3);
            const uint32_t base = stage + row * 128 + ((((lane >> 4) ^ lane) & 7) << 4);
            const int out_row = ((kTilesPerCta - 1) * kNumCtas + tile0) * 128 + wg * 64 + (wtid >> 5) * 16;
#pragma unroll
            for (int h = 0; h < 2; ++h) {
#pragma unroll
                for (int i = 16 * h; i < 16 * h + 16; i += 2) {
                    const uint32_t r0 = pack_bf16(o[4 * i] * inv0, o[4 * i + 1] * inv0);
                    const uint32_t r1 = pack_bf16(o[4 * i + 2] * inv1, o[4 * i + 3] * inv1);
                    const uint32_t r2 = pack_bf16(o[4 * i + 4] * inv0, o[4 * i + 5] * inv0);
                    const uint32_t r3 = pack_bf16(o[4 * i + 6] * inv1, o[4 * i + 7] * inv1);
                    const uint32_t addr = (base ^ ((i & 7) << 4)) + (i >> 3) * 2048;
                    asm volatile("stmatrix.sync.aligned.m8n8.x4.shared.b16 [%0], {%1, %2, %3, %4};"
                                 ::"r"(addr), "r"(r0), "r"(r1), "r"(r2), "r"(r3) : "memory");
                }
                asm volatile("fence.proxy.async.shared::cta;" ::: "memory");
                __syncwarp();
                if (lane == 0) tma_store(&map_o16, stage + h * 4096, out_row, 2 * h);
            }
            if (lane == 0) asm volatile("cp.async.bulk.wait_group.read 0;" ::: "memory");
            TR(3, 4 + wg);
        }
    }
}

typedef CUresult (*EncodeTiledFn)(CUtensorMap*, CUtensorMapDataType, cuuint32_t, void*, const cuuint64_t*,
                                  const cuuint64_t*, const cuuint32_t*, const cuuint32_t*, CUtensorMapInterleave,
                                  CUtensorMapSwizzle, CUtensorMapL2promotion, CUtensorMapFloatOOBfill);

void make_map(EncodeTiledFn enc, CUtensorMap* map, const void* ptr, uint32_t box_rows, uint32_t box_chunks) {
    const cuuint64_t dims[3] = {64, (cuuint64_t)kRows, 4};
    const cuuint64_t strides[2] = {512, 128};
    const cuuint32_t box[3] = {64, box_rows, box_chunks};
    const cuuint32_t estr[3] = {1, 1, 1};
    enc(map, CU_TENSOR_MAP_DATA_TYPE_BFLOAT16, 3, const_cast<void*>(ptr), dims, strides, box, estr,
        CU_TENSOR_MAP_INTERLEAVE_NONE, CU_TENSOR_MAP_SWIZZLE_128B, CU_TENSOR_MAP_L2_PROMOTION_L2_128B,
        CU_TENSOR_MAP_FLOAT_OOB_FILL_NONE);
}

}

extern "C" void kernel_launch(void* const* d_in, const int* in_sizes, int n_in, void* d_out, int out_size) {
    (void)in_sizes; (void)n_in; (void)out_size;
    static EncodeTiledFn enc = nullptr;
    if (!enc) {
        void* fn = nullptr;
        cudaDriverEntryPointQueryResult st;
        cudaGetDriverEntryPoint("cuTensorMapEncodeTiled", &fn, cudaEnableDefault, &st);
        enc = (EncodeTiledFn)fn;
        cudaFuncSetAttribute(gqa_fwd_kernel, cudaFuncAttributeMaxDynamicSharedMemorySize, kSmemBytes);
    }
    CUtensorMap mq, mk, mv, mo, mo16;
    make_map(enc, &mq, d_in[0], 64, 2);
    make_map(enc, &mk, d_in[1], 128, 1);
    make_map(enc, &mv, d_in[2], 64, 2);
    make_map(enc, &mo, d_out, 64, 4);
    make_map(enc, &mo16, d_out, 16, 2);
    gqa_fwd_kernel<<<kNumCtas, 384, kSmemBytes, cudaStreamPerThread>>>(
        mq, mk, mv, mo, mo16, (const uint8_t*)d_in[0], (const uint8_t*)d_in[1],
        (const uint8_t*)d_in[2]);
}
```

```cpp
#include <cuda.h>
#include <cuda_bf16.h>
#include <cuda_runtime.h>
#include <stdint.h>

namespace {

constexpr int kRows = 32768;
constexpr int kTilesPerCta = 2;
constexpr int kNumCtas = 128;
constexpr int kSlotBytes = 32768;
constexpr int kNumSlots = 5;
constexpr int kItemsPerTile = 16;
constexpr int kNumItems = kItemsPerTile * kTilesPerCta;
constexpr int kNumBlocks = 4 * kTilesPerCta;

constexpr int kSmemQ = 0;
constexpr int kSmemRing = 65536;
constexpr int kSmemBar = kSmemRing + kNumSlots * kSlotBytes;
constexpr int kSmemBytes = kSmemBar + 256;

constexpr int kBarFull = 0;
constexpr int kBarEmpty = 40;
constexpr int kBarQFull = 80;
constexpr int kBarQEmpty = 112;
constexpr int kBarStageOk = 128;
constexpr int kBarStaged = 144;
constexpr int kBarPrefetchGo = 160;
constexpr int kNamedTurn = 1;

constexpr float kScaleLog2 = 0.0625f * 1.4426950408889634f;
constexpr float kLazyLog2 = 8.0f;
constexpr float kLazyRaw = kLazyLog2 / kScaleLog2;
constexpr float kLazySum = 256.0f;

constexpr int kStagger = 1500;
constexpr int kStartWindow = 4;
constexpr int kStartWindowLate = 3;
constexpr int kPrefetchQAt = 9;
constexpr int kPrefetchKvAt = 16;
constexpr int kStepsBeforePv = 6;
constexpr int kFinalParts = 4;

__device__ __forceinline__ uint32_t smem_u32(const void* p) { return (uint32_t)__cvta_generic_to_shared(p); }

__device__ __forceinline__ void mbar_init(uint32_t bar, uint32_t count) {
    asm volatile("mbarrier.init.shared::cta.b64 [%0], %1;" ::"r"(bar), "r"(count) : "memory");
}
__device__ __forceinline__ void mbar_expect_tx(uint32_t bar, uint32_t bytes) {
    asm volatile("mbarrier.arrive.expect_tx.shared::cta.b64 _, [%0], %1;" ::"r"(bar), "r"(bytes) : "memory");
}
__device__ __forceinline__ void mbar_arrive(uint32_t bar) {
    asm volatile("mbarrier.arrive.shared::cta.b64 _, [%0];" ::"r"(bar) : "memory");
}
__device__ __forceinline__ void mbar_arrive_cta(uint32_t bar, uint32_t cta) {
    asm volatile(
        "{\n.reg .b32 ra;\nmapa.shared::cluster.u32 ra, %0, %1;\n"
        "mbarrier.arrive.shared::cluster.b64 _, [ra];\n}\n" ::"r"(bar), "r"(cta) : "memory");
}
__device__ __forceinline__ void mbar_wait(uint32_t bar, uint32_t parity) {
    asm volatile(
        "{\n.reg .pred p;\n"
        "LAB_WAIT:\n"
        "mbarrier.try_wait.parity.shared::cta.b64 p, [%0], %1;\n"
        "@p bra LAB_DONE;\n"
        "bra LAB_WAIT;\n"
        "LAB_DONE:\n}\n" ::"r"(bar), "r"(parity) : "memory");
}
__device__ __forceinline__ void mbar_wait_bounded(uint32_t bar, uint32_t parity) {
    asm volatile(
        "{\n.reg .pred p;\n.reg .u32 n;\n"
        "mov.u32 n, 0;\n"
        "LAB_WAIT:\n"
        "mbarrier.try_wait.parity.shared::cta.b64 p, [%0], %1;\n"
        "@p bra LAB_DONE;\n"
        "add.u32 n, n, 1;\n"
        "setp.lt.u32 p, n, 0x4000000;\n"
        "@p bra LAB_WAIT;\n"
        "trap;\n"
        "LAB_DONE:\n}\n" ::"r"(bar), "r"(parity) : "memory");
}
__device__ __forceinline__ void named_sync(int id, int n) { asm volatile("bar.sync %0, %1;" ::"r"(id), "r"(n) : "memory"); }
__device__ __forceinline__ void named_arrive(int id, int n) { asm volatile("bar.arrive %0, %1;" ::"r"(id), "r"(n) : "memory"); }

__device__ __forceinline__ void tma_load(uint32_t dst, const CUtensorMap* map, uint32_t bar, int row, int chunk) {
    asm volatile(
        "cp.async.bulk.tensor.3d.shared::cluster.global.mbarrier::complete_tx::bytes [%0], [%1, {%3, %4, %5}], [%2];"
        ::"r"(dst), "l"(map), "r"(bar), "r"(0), "r"(row), "r"(chunk) : "memory");
}
__device__ __forceinline__ void tma_load_mc(uint32_t dst, const CUtensorMap* map, uint32_t bar, int row, int chunk) {
    asm volatile(
        "cp.async.bulk.tensor.3d.shared::cluster.global.mbarrier::complete_tx::bytes.multicast::cluster"
        " [%0], [%1, {%3, %4, %5}], [%2], %6;"
        ::"r"(dst), "l"(map), "r"(bar), "r"(0), "r"(row), "r"(chunk), "h"((uint16_t)3) : "memory");
}
__device__ __forceinline__ void tma_store(const CUtensorMap* map, uint32_t src, int row, int chunk) {
    asm volatile("cp.async.bulk.tensor.3d.global.shared::cta.bulk_group [%0, {%2, %3, %4}], [%1];"
                 ::"l"(map), "r"(src), "r"(0), "r"(row), "r"(chunk) : "memory");
    asm volatile("cp.async.bulk.commit_group;" ::: "memory");
}
__device__ __forceinline__ void prefetch_map(const CUtensorMap* map) {
    asm volatile("prefetch.tensormap [%0];" ::"l"(map) : "memory");
}
__device__ __forceinline__ uint32_t l2_localize(const uint8_t* p) {
    uint32_t v;
    asm volatile("ld.volatile.global.L2::256B.b32 %0, [%1];" : "=r"(v) : "l"(p) : "memory");
    return v;
}
__device__ __forceinline__ void wgmma_fence() { asm volatile("wgmma.fence.sync.aligned;" ::: "memory"); }
__device__ __forceinline__ void wgmma_commit() { asm volatile("wgmma.commit_group.sync.aligned;" ::: "memory"); }
template <int N>
__device__ __forceinline__ void wgmma_wait() { asm volatile("wgmma.wait_group.sync.aligned %0;" ::"n"(N) : "memory"); }

template <int N>
__device__ __forceinline__ void pin_regs(float (&r)[N]) {
#pragma unroll
    for (int i = 0; i < N; ++i) asm volatile("" : "+f"(r[i])::"memory");
}

__device__ __forceinline__ float ex2(float x) {
    float y;
    asm("ex2.approx.ftz.f32 %0, %1;" : "=f"(y) : "f"(x));
    return y;
}
__device__ __forceinline__ float rcp(float x) {
    float y;
    asm("rcp.approx.ftz.f32 %0, %1;" : "=f"(y) : "f"(x));
    return y;
}
__device__ __forceinline__ uint32_t pack_bf16(float lo, float hi) {
    uint32_t r;
    asm("cvt.rn.bf16x2.f32 %0, %1, %2;" : "=r"(r) : "f"(hi), "f"(lo));
    return r;
}
__device__ __forceinline__ void stage_blocks(const float* o, float inv0, float inv1, uint32_t addr) {
    const uint32_t r0 = pack_bf16(o[0] * inv0, o[1] * inv0);
    const uint32_t r1 = pack_bf16(o[2] * inv1, o[3] * inv1);
    const uint32_t r2 = pack_bf16(o[4] * inv0, o[5] * inv0);
    const uint32_t r3 = pack_bf16(o[6] * inv1, o[7] * inv1);
    asm volatile("stmatrix.sync.aligned.m8n8.x4.shared.b16 [%0], {%1, %2, %3, %4};"
                 ::"r"(addr), "r"(r0), "r"(r1), "r"(r2), "r"(r3) : "memory");
}

__device__ __forceinline__ bool upper_half_above(const float (&s)[64], float t0, float t1) {
    uint32_t r;
    asm("{\n.reg .pred a, b, c, d;\n"
        "setp.gtu.f32 a, %1, %33;\nsetp.gtu.f32 b, %2, %33;\nsetp.gtu.f32 c, %3, %34;\nsetp.gtu.f32 d, %4, %34;\n"
        "setp.gtu.or.f32 a, %5, %33, a;\nsetp.gtu.or.f32 b, %6, %33, b;\nsetp.gtu.or.f32 c, %7, %34, c;\nsetp.gtu.or.f32 d, %8, %34, d;\n"
        "setp.gtu.or.f32 a, %9, %33, a;\nsetp.gtu.or.f32 b, %10, %33, b;\nsetp.gtu.or.f32 c, %11, %34, c;\nsetp.gtu.or.f32 d, %12, %34, d;\n"
        "setp.gtu.or.f32 a, %13, %33, a;\nsetp.gtu.or.f32 b, %14, %33, b;\nsetp.gtu.or.f32 c, %15, %34, c;\nsetp.gtu.or.f32 d, %16, %34, d;\n"
        "setp.gtu.or.f32 a, %17, %33, a;\nsetp.gtu.or.f32 b, %18, %33, b;\nsetp.gtu.or.f32 c, %19, %34, c;\nsetp.gtu.or.f32 d, %20, %34, d;\n"
        "setp.gtu.or.f32 a, %21, %33, a;\nsetp.gtu.or.f32 b, %22, %33, b;\nsetp.gtu.or.f32 c, %23, %34, c;\nsetp.gtu.or.f32 d, %24, %34, d;\n"
        "setp.gtu.or.f32 a, %25, %33, a;\nsetp.gtu.or.f32 b, %26, %33, b;\nsetp.gtu.or.f32 c, %27, %34, c;\nsetp.gtu.or.f32 d, %28, %34, d;\n"
        "setp.gtu.or.f32 a, %29, %33, a;\nsetp.gtu.or.f32 b, %30, %33, b;\nsetp.gtu.or.f32 c, %31, %34, c;\nsetp.gtu.or.f32 d, %32, %34, d;\n"
        "or.pred a, a, b;\nor.pred c, c, d;\nor.pred a, a, c;\nselp.u32 %0, 1, 0, a;\n}\n"
        : "=r"(r)
        :
        "f"(s[32]), "f"(s[33]), "f"(s[34]), "f"(s[35]), "f"(s[36]), "f"(s[37]), "f"(s[38]), "f"(s[39]),
        "f"(s[40]), "f"(s[41]), "f"(s[42]), "f"(s[43]), "f"(s[44]), "f"(s[45]), "f"(s[46]), "f"(s[47]),
        "f"(s[48]), "f"(s[49]), "f"(s[50]), "f"(s[51]), "f"(s[52]), "f"(s[53]), "f"(s[54]), "f"(s[55]),
        "f"(s[56]), "f"(s[57]), "f"(s[58]), "f"(s[59]), "f"(s[60]), "f"(s[61]), "f"(s[62]), "f"(s[63]),
        "f"(t0), "f"(t1));
    return r != 0;
}

__device__ __forceinline__ uint32_t desc_lo(uint32_t addr, uint32_t lbo_bytes) {
    return ((addr & 0x3FFFF) >> 4) | ((lbo_bytes >> 4) << 16);
}
__device__ __forceinline__ uint64_t desc64(uint32_t lo) {
    uint64_t d;
    asm("mov.b64 %0, {%1, %2};" : "=l"(d) : "r"(lo), "r"(0x40000040u));
    return d;
}

__device__ __forceinline__ void wgmma_ss_n128(float (&d)[64], uint64_t desc_a, uint64_t desc_b, int accumulate) {
    asm volatile(
        "{\n.reg .pred p;\nsetp.ne.b32 p, %66, 0;\n"
        "wgmma.mma_async.sync.aligned.m64n128k16.f32.bf16.bf16 {"
        "%0, %1, %2, %3, %4, %5, %6, %7, %8, %9, %10, %11, %12, %13, %14, %15, "
        "%16, %17, %18, %19, %20, %21, %22, %23, %24, %25, %26, %27, %28, %29, %30, %31, "
        "%32, %33, %34, %35, %36, %37, %38, %39, %40, %41, %42, %43, %44, %45, %46, %47, "
        "%48, %49, %50, %51, %52, %53, %54, %55, %56, %57, %58, %59, %60, %61, %62, %63"
        "}, %64, %65, p, 1, 1, 0, 0;\n}\n"
        :
        "+f"(d[0]), "+f"(d[1]), "+f"(d[2]), "+f"(d[3]), "+f"(d[4]), "+f"(d[5]), "+f"(d[6]), "+f"(d[7]),
        "+f"(d[8]), "+f"(d[9]), "+f"(d[10]), "+f"(d[11]), "+f"(d[12]), "+f"(d[13]), "+f"(d[14]), "+f"(d[15]),
        "+f"(d[16]), "+f"(d[17]), "+f"(d[18]), "+f"(d[19]), "+f"(d[20]), "+f"(d[21]), "+f"(d[22]), "+f"(d[23]),
        "+f"(d[24]), "+f"(d[25]), "+f"(d[26]), "+f"(d[27]), "+f"(d[28]), "+f"(d[29]), "+f"(d[30]), "+f"(d[31]),
        "+f"(d[32]), "+f"(d[33]), "+f"(d[34]), "+f"(d[35]), "+f"(d[36]), "+f"(d[37]), "+f"(d[38]), "+f"(d[39]),
        "+f"(d[40]), "+f"(d[41]), "+f"(d[42]), "+f"(d[43]), "+f"(d[44]), "+f"(d[45]), "+f"(d[46]), "+f"(d[47]),
        "+f"(d[48]), "+f"(d[49]), "+f"(d[50]), "+f"(d[51]), "+f"(d[52]), "+f"(d[53]), "+f"(d[54]), "+f"(d[55]),
        "+f"(d[56]), "+f"(d[57]), "+f"(d[58]), "+f"(d[59]), "+f"(d[60]), "+f"(d[61]), "+f"(d[62]), "+f"(d[63])
        : "l"(desc_a), "l"(desc_b), "r"(accumulate));
}

__device__ __forceinline__ void wgmma_rs_n256_x4(float (&d)[128], const uint32_t* a, uint32_t desc_lo, int accumulate,
                                                 int again) {
    asm volatile(
        "{\n.reg .pred p, q, t;\n.reg .b32 lo;\n.reg .b64 d0, d1, d2, d3;\n"
        "setp.ne.b32 p, %145, 0;\nsetp.ne.b32 q, %146, 0;\nsetp.eq.b32 t, 0, 0;\n"
        "mov.b64 d0, {%144, 0x40000040};\n"
        "add.u32 lo, %144, 128;\nmov.b64 d1, {lo, 0x40000040};\n"
        "add.u32 lo, %144, 256;\nmov.b64 d2, {lo, 0x40000040};\n"
        "add.u32 lo, %144, 384;\nmov.b64 d3, {lo, 0x40000040};\n"
        "GROUP:\n"
        "wgmma.fence.sync.aligned;\n"
        "wgmma.mma_async.sync.aligned.m64n256k16.f32.bf16.bf16 {"
        "%0, %1, %2, %3, %4, %5, %6, %7, %8, %9, %10, %11, %12, %13, %14, %15, "
        "%16, %17, %18, %19, %20, %21, %22, %23, %24, %25, %26, %27, %28, %29, %30, %31, "
        "%32, %33, %34, %35, %36, %37, %38, %39, %40, %41, %42, %43, %44, %45, %46, %47, "
        "%48, %49, %50, %51, %52, %53, %54, %55, %56, %57, %58, %59, %60, %61, %62, %63, "
        "%64, %65, %66, %67, %68, %69, %70, %71, %72, %73, %74, %75, %76, %77, %78, %79, "
        "%80, %81, %82, %83, %84, %85, %86, %87, %88, %89, %90, %91, %92, %93, %94, %95, "
        "%96, %97, %98, %99, %100, %101, %102, %103, %104, %105, %106, %107, %108, %109, %110, %111, "
        "%112, %113, %114, %115, %116, %117, %118, %119, %120, %121, %122, %123, %124, %125, %126, %127"
        "}, {%128, %129, %130, %131}, d0, p, 1, 1, 1;\n"
        "wgmma.mma_async.sync.aligned.m64n256k16.f32.bf16.bf16 {"
        "%0, %1, %2, %3, %4, %5, %6, %7, %8, %9, %10, %11, %12, %13, %14, %15, "
        "%16, %17, %18, %19, %20, %21, %22, %23, %24, %25, %26, %27, %28, %29, %30, %31, "
        "%32, %33, %34, %35, %36, %37, %38, %39, %40, %41, %42, %43, %44, %45, %46, %47, "
        "%48, %49, %50, %51, %52, %53, %54, %55, %56, %57, %58, %59, %60, %61, %62, %63, "
        "%64, %65, %66, %67, %68, %69, %70, %71, %72, %73, %74, %75, %76, %77, %78, %79, "
        "%80, %81, %82, %83, %84, %85, %86, %87, %88, %89, %90, %91, %92, %93, %94, %95, "
        "%96, %97, %98, %99, %100, %101, %102, %103, %104, %105, %106, %107, %108, %109, %110, %111, "
        "%112, %113, %114, %115, %116, %117, %118, %119, %120, %121, %122, %123, %124, %125, %126, %127"
        "}, {%132, %133, %134, %135}, d1, t, 1, 1, 1;\n"
        "wgmma.mma_async.sync.aligned.m64n256k16.f32.bf16.bf16 {"
        "%0, %1, %2, %3, %4, %5, %6, %7, %8, %9, %10, %11, %12, %13, %14, %15, "
        "%16, %17, %18, %19, %20, %21, %22, %23, %24, %25, %26, %27, %28, %29, %30, %31, "
        "%32, %33, %34, %35, %36, %37, %38, %39, %40, %41, %42, %43, %44, %45, %46, %47, "
        "%48, %49, %50, %51, %52, %53, %54, %55, %56, %57, %58, %59, %60, %61, %62, %63, "
        "%64, %65, %66, %67, %68, %69, %70, %71, %72, %73, %74, %75, %76, %77, %78, %79, "
        "%80, %81, %82, %83, %84, %85, %86, %87, %88, %89, %90, %91, %92, %93, %94, %95, "
        "%96, %97, %98, %99, %100, %101, %102, %103, %104, %105, %106, %107, %108, %109, %110, %111, "
        "%112, %113, %114, %115, %116, %117, %118, %119, %120, %121, %122, %123, %124, %125, %126, %127"
        "}, {%136, %137, %138, %139}, d2, t, 1, 1, 1;\n"
        "wgmma.mma_async.sync.aligned.m64n256k16.f32.bf16.bf16 {"
        "%0, %1, %2, %3, %4, %5, %6, %7, %8, %9, %10, %11, %12, %13, %14, %15, "
        "%16, %17, %18, %19, %20, %21, %22, %23, %24, %25, %26, %27, %28, %29, %30, %31, "
        "%32, %33, %34, %35, %36, %37, %38, %39, %40, %41, %42, %43, %44, %45, %46, %47, "
        "%48, %49, %50, %51, %52, %53, %54, %55, %56, %57, %58, %59, %60, %61, %62, %63, "
        "%64, %65, %66, %67, %68, %69, %70, %71, %72, %73, %74, %75, %76, %77, %78, %79, "
        "%80, %81, %82, %83, %84, %85, %86, %87, %88, %89, %90, %91, %92, %93, %94, %95, "
        "%96, %97, %98, %99, %100, %101, %102, %103, %104, %105, %106, %107, %108, %109, %110, %111, "
        "%112, %113, %114, %115, %116, %117, %118, %119, %120, %121, %122, %123, %124, %125, %126, %127"
        "}, {%140, %141, %142, %143}, d3, t, 1, 1, 1;\n"
        "wgmma.commit_group.sync.aligned;\n"
        "@q bra GROUP;\n}\n"
        :
        "+f"(d[0]), "+f"(d[1]), "+f"(d[2]), "+f"(d[3]), "+f"(d[4]), "+f"(d[5]), "+f"(d[6]), "+f"(d[7]),
        "+f"(d[8]), "+f"(d[9]), "+f"(d[10]), "+f"(d[11]), "+f"(d[12]), "+f"(d[13]), "+f"(d[14]), "+f"(d[15]),
        "+f"(d[16]), "+f"(d[17]), "+f"(d[18]), "+f"(d[19]), "+f"(d[20]), "+f"(d[21]), "+f"(d[22]), "+f"(d[23]),
        "+f"(d[24]), "+f"(d[25]), "+f"(d[26]), "+f"(d[27]), "+f"(d[28]), "+f"(d[29]), "+f"(d[30]), "+f"(d[31]),
        "+f"(d[32]), "+f"(d[33]), "+f"(d[34]), "+f"(d[35]), "+f"(d[36]), "+f"(d[37]), "+f"(d[38]), "+f"(d[39]),
        "+f"(d[40]), "+f"(d[41]), "+f"(d[42]), "+f"(d[43]), "+f"(d[44]), "+f"(d[45]), "+f"(d[46]), "+f"(d[47]),
        "+f"(d[48]), "+f"(d[49]), "+f"(d[50]), "+f"(d[51]), "+f"(d[52]), "+f"(d[53]), "+f"(d[54]), "+f"(d[55]),
        "+f"(d[56]), "+f"(d[57]), "+f"(d[58]), "+f"(d[59]), "+f"(d[60]), "+f"(d[61]), "+f"(d[62]), "+f"(d[63]),
        "+f"(d[64]), "+f"(d[65]), "+f"(d[66]), "+f"(d[67]), "+f"(d[68]), "+f"(d[69]), "+f"(d[70]), "+f"(d[71]),
        "+f"(d[72]), "+f"(d[73]), "+f"(d[74]), "+f"(d[75]), "+f"(d[76]), "+f"(d[77]), "+f"(d[78]), "+f"(d[79]),
        "+f"(d[80]), "+f"(d[81]), "+f"(d[82]), "+f"(d[83]), "+f"(d[84]), "+f"(d[85]), "+f"(d[86]), "+f"(d[87]),
        "+f"(d[88]), "+f"(d[89]), "+f"(d[90]), "+f"(d[91]), "+f"(d[92]), "+f"(d[93]), "+f"(d[94]), "+f"(d[95]),
        "+f"(d[96]), "+f"(d[97]), "+f"(d[98]), "+f"(d[99]), "+f"(d[100]), "+f"(d[101]), "+f"(d[102]), "+f"(d[103]),
        "+f"(d[104]), "+f"(d[105]), "+f"(d[106]), "+f"(d[107]), "+f"(d[108]), "+f"(d[109]), "+f"(d[110]), "+f"(d[111]),
        "+f"(d[112]), "+f"(d[113]), "+f"(d[114]), "+f"(d[115]), "+f"(d[116]), "+f"(d[117]), "+f"(d[118]), "+f"(d[119]),
        "+f"(d[120]), "+f"(d[121]), "+f"(d[122]), "+f"(d[123]), "+f"(d[124]), "+f"(d[125]), "+f"(d[126]), "+f"(d[127])
        :
        "r"(a[0]), "r"(a[1]), "r"(a[2]), "r"(a[3]), "r"(a[4]), "r"(a[5]), "r"(a[6]), "r"(a[7]),
        "r"(a[8]), "r"(a[9]), "r"(a[10]), "r"(a[11]), "r"(a[12]), "r"(a[13]), "r"(a[14]), "r"(a[15]),
        "r"(desc_lo), "r"(accumulate), "r"(again)
        : "memory");
}


__device__ __forceinline__ uint32_t slot_of(int i) {
    const uint64_t t = i < 16 ? 0x0432104321043210ull : 0x2301423014231421ull;
    return (uint32_t)(t >> (4 * (i & 15))) & 7;
}
__device__ __forceinline__ uint32_t phase_of(int i) { return (0x6c9783e0u >> i) & 1; }
__device__ __forceinline__ uint32_t block_config(int it) {
    const uint64_t t = it < 4 ? 0x811a3223e4440688ull : 0x64c1c89893137311ull;
    return (uint32_t)(t >> (16 * (it & 3))) & 0xFFFF;
}
constexpr int kStageSlot0 = 3, kStageSlot1 = 0;
constexpr int kStoreAAt = 19, kStoreADoneAt = 20, kStoreBAt = 22, kStoreBDoneAt = 23;

__device__ __forceinline__ int tile_of_cta(int block) {
    const int c = block >> 1;
    int group, sub;
    if (c < 4)       { group = 30 + ((c == 1 || c == 2) ? 1 : 0); sub = c >> 1; }
    else if (c < 36) { const int u = c - 4;  group = ((u >> 4) << 3) + (u & 7); sub = (u >> 3) & 1; }
    else             { const int u = c - 36; const int h = u >= 14, v = u - 14 * h; sub = v >= 7; group = 16 + 7 * h + v - 7 * sub; }
    return group * 4 + sub * 2 + (block & 1);
}

__global__ void __cluster_dims__(2, 1, 1) __launch_bounds__(384, 1)
gqa_fwd_kernel(const __grid_constant__ CUtensorMap map_q, const __grid_constant__ CUtensorMap map_k,
               const __grid_constant__ CUtensorMap map_v, const __grid_constant__ CUtensorMap map_o,
               const __grid_constant__ CUtensorMap map_o16,
               const uint8_t* __restrict__ gq, const uint8_t* __restrict__ gk, const uint8_t* __restrict__ gv) {
    extern __shared__ __align__(1024) uint8_t smem_raw[];
    const uint32_t smem = smem_u32(smem_raw);
    const uint32_t bars = smem + kSmemBar;
    const int tid = threadIdx.x;
    const int wg = __shfl_sync(0xffffffffu, tid >> 7, 0);
    const uint32_t cta_rank = blockIdx.x & 1;
    const int tile0 = tile_of_cta(blockIdx.x);

    const int group0 = tile0 >> 2;
    const bool late = (group0 < 16) ? (group0 >= 8) : (group0 < 30 ? group0 >= 23 : group0 == 31);
    const int delay = late ? kStagger : 0;
    const long long t_start = clock64();
    if (wg < 2) while (clock64() - t_start < delay) {}
    if (wg == 0) l2_localize(gq + (size_t)tile0 * 65536 + tid * 256);
    if (wg == 1) l2_localize(gk + (size_t)(tile0 >> 2) * 262144 + cta_rank * 32768 + (tid & 127) * 256);
    if (tid == 256) {
        prefetch_map(&map_q);
        prefetch_map(&map_k);
        prefetch_map(&map_v);
        prefetch_map(&map_o);
        prefetch_map(&map_o16);
        for (int s = 0; s < kNumSlots; ++s) {
            mbar_init(bars + kBarFull + 8 * s, 1);
            mbar_init(bars + kBarEmpty + 8 * s, 4);
        }
        for (int w = 0; w < 2; ++w) {
            mbar_init(bars + kBarQFull + 16 * w, 1);
            mbar_init(bars + kBarQFull + 16 * w + 8, 1);
            mbar_init(bars + kBarQEmpty + 8 * w, 1);
            mbar_init(bars + kBarStageOk + 8 * w, 1);
            mbar_init(bars + kBarStaged + 8 * w, 4);
        }
        mbar_init(bars + kBarPrefetchGo, 1);
        mbar_init(bars + kBarPrefetchGo + 8, 1);
        asm volatile("fence.mbarrier_init.release.cluster;" ::: "memory");
    }
    __syncthreads();
    asm volatile("barrier.cluster.arrive.relaxed.aligned;" ::: "memory");

    if (wg == 2) {
        asm volatile("setmaxnreg.dec.sync.aligned.u32 24;");
        const int warp = (tid >> 5) & 3;
        if (warp == 0) {
            auto load_q = [&](int t, int w, int h) {
                const uint32_t bar = bars + kBarQFull + 16 * w + 8 * h;
                mbar_expect_tx(bar, 16384);
                tma_load(smem + kSmemQ + w * 32768 + h * 16384, &map_q, bar,
                         (t * kNumCtas + tile0) * 128 + w * 64, 2 * h);
            };
            auto load_kv = [&](int i, uint32_t slot) {
                const int t = i >> 4, j = (i >> 2) & 3, kind = i & 3;
                const int kv_row = (((t * kNumCtas + tile0) >> 2) << 9) + j * 128;
                const uint32_t full = bars + kBarFull + 8 * slot;
                const uint32_t dst = smem + kSmemRing + slot * kSlotBytes + cta_rank * 16384;
                mbar_expect_tx(full, kSlotBytes);
                if (kind < 2) tma_load_mc(dst, &map_k, full, kv_row, kind * 2 + cta_rank);
                else          tma_load_mc(dst, &map_v, full, kv_row + (kind - 2) * 64, cta_rank * 2);
            };
            const bool leader = (tid & 31) == 0;
            while (clock64() - t_start < delay) {}
            if (leader) load_q(0, 0, 0);
            __syncwarp();
            asm volatile("barrier.cluster.wait.aligned;" ::: "memory");
            if (leader) {
                auto start_bar = [&](int n) -> uint32_t {
                    if (n == 0) return bars + kBarQFull;
                    if (n == 2) return bars + kBarQFull + 8;
                    if (n == 4) return bars + kBarQFull + 16;
                    if (n == 5) return bars + kBarQFull + 24;
                    return bars + kBarFull + 8 * (n < 4 ? (n >> 1) : (n - 4));
                };
#pragma unroll
                for (int n = 1; n < 9; ++n) {
                    const int window = late ? kStartWindowLate : kStartWindow;
                    if (n >= window) mbar_wait_bounded(start_bar(n - window), 0);
                    if (n == 8) mbar_wait_bounded(start_bar(6), 0);
                    if (n == 2) load_q(0, 0, 1);
                    else if (n == 4) load_q(0, 1, 0);
                    else if (n == 5) load_q(0, 1, 1);
                    else load_kv(n < 4 ? (n >> 1) : (n - 4), n < 4 ? (n >> 1) : (n - 4));
                }
                auto store_out = [&](int w) {
                    mbar_wait_bounded(bars + kBarStaged + 8 * w, 0);
                    tma_store(&map_o, smem + kSmemRing + (w == 0 ? kStageSlot0 : kStageSlot1) * kSlotBytes,
                              tile0 * 128 + w * 64, 0);
                };
                auto store_done = [&](int w) {
                    asm volatile("cp.async.bulk.wait_group.read 0;" ::: "memory");
                    const uint32_t bar = bars + kBarEmpty + 8 * (w == 0 ? kStageSlot0 : kStageSlot1);
                    mbar_arrive_cta(bar, 0);
                    mbar_arrive_cta(bar, 1);
                };
#pragma unroll 1
                for (int i = kNumSlots; i < kNumItems; ++i) {
                    if (i == kPrefetchQAt) mbar_arrive(bars + kBarPrefetchGo);
                    if (i == kPrefetchKvAt) mbar_arrive(bars + kBarPrefetchGo + 8);
                    if (i == kItemsPerTile + 1) { mbar_wait_bounded(bars + kBarQEmpty, 0); load_q(1, 0, 0); load_q(1, 0, 1); }
                    if (i == kItemsPerTile + 2) { mbar_wait_bounded(bars + kBarQEmpty + 8, 0); load_q(1, 1, 0); load_q(1, 1, 1); }
                    if (i == kStoreAAt) store_out(0);
                    if (i == kStoreADoneAt) store_done(0);
                    if (i == kStoreBAt) store_out(1);
                    if (i == kStoreBDoneAt) store_done(1);
                    const uint32_t slot = slot_of(i);
                    mbar_wait_bounded(bars + kBarEmpty + 8 * slot, phase_of(i) ^ 1);
                    load_kv(i, slot);
                }
            }
        } else {
            asm volatile("barrier.cluster.wait.aligned;" ::: "memory");
            if (warp == 1) {
                mbar_wait_bounded(bars + kBarPrefetchGo, 0);
#pragma unroll 1
                for (int i = 0; i < 8; ++i)
                    l2_localize(gq + (size_t)(kNumCtas + tile0) * 65536 + i * 8192 + (tid & 31) * 256);
                mbar_wait_bounded(bars + kBarPrefetchGo + 8, 0);
                const size_t off = (size_t)((kNumCtas + tile0) >> 2) * 262144 + (tile0 & 3) * 16384 + (tid & 31) * 256;
                l2_localize(gv + off);
                l2_localize(gv + off + 8192);
                l2_localize(gk + off + 65536);
                l2_localize(gk + off + 65536 + 8192);
            }
        }
    } else {
        asm volatile("setmaxnreg.inc.sync.aligned.u32 240;");
        asm volatile("barrier.cluster.wait.aligned;" ::: "memory");
        const int lane = tid & 31;
        const int wtid = tid & 127;
        const int my_turn = kNamedTurn + wg, other_turn = kNamedTurn + (wg ^ 1);
        const uint32_t desc_q = desc_lo(smem + kSmemQ + wg * 32768, 16);
        const uint32_t desc_k0 = desc_lo(smem + kSmemRing, 16);
        const uint32_t desc_v0 = desc_lo(smem + kSmemRing, 8192);
        const int never = (int)(reinterpret_cast<uintptr_t>(gq) & 1);

        uint32_t empty_remote;
        asm("mapa.shared::cluster.u32 %0, %1, %2;" : "=r"(empty_remote) : "r"(bars + kBarEmpty), "r"(wtid & 1));
        auto arrive_if = [&](bool p, uint32_t cluster_addr) {
            asm volatile("{\n.reg .pred p;\nsetp.ne.b32 p, %1, 0;\n@p mbarrier.arrive.shared::cluster.b64 _, [%0];\n}\n"
                         ::"r"(cluster_addr), "r"((int)p) : "memory");
        };
        auto arrive_local_if = [&](bool p, uint32_t bar) {
            asm volatile("{\n.reg .pred p;\nsetp.ne.b32 p, %1, 0;\n@p mbarrier.arrive.shared::cta.b64 _, [%0];\n}\n"
                         ::"r"(bar), "r"((int)p) : "memory");
        };

        if (wg == 1) named_arrive(kNamedTurn, 256);

        float o[128];
        float m0 = 0.f, m1 = 0.f, l0 = 0.f, l1 = 0.f, inv0 = 0.f, inv1 = 0.f;

        auto key_block = [&](const int it, const uint32_t cfg) {
            const int t = it >> 2, j = it & 3;
            const int item = it * 4;

            float s[64];
            const uint32_t ka = cfg & 7, kb = (cfg >> 3) & 7, va = (cfg >> 6) & 7, vb = (cfg >> 9) & 7;
            const uint32_t ka_ph = (cfg >> 12) & 1, kb_ph = (cfg >> 13) & 1, va_ph = (cfg >> 14) & 1, vb_ph = cfg >> 15;

            if (j == 0) {
                l0 = l1 = 0.f;
            }
            if (it != kItemsPerTile / 4) {
                if (j == 0) mbar_wait(bars + kBarQFull + 16 * wg, t);
                mbar_wait(bars + kBarFull + 8 * ka, ka_ph);
            }
            const bool more = item + kNumSlots + 1 < kNumItems;
            const bool rel_ka = wtid < 2 && more;
            const bool rel_kb = wtid < 2 && more && !(it == 3 && wg == 0);
            const bool sig_k = it == 3 && (wtid == 0 || (wtid == 1 && wg == 1));
            const uint32_t sig_k_bar = wtid == 0 ? bars + kBarQEmpty + 8 * wg : bars + kBarStageOk;
            const uint32_t dk_first = desc_k0 + ka * (kSlotBytes >> 4);
            named_sync(my_turn | (dk_first & (0u - never)), 256);
            wgmma_fence();
            {
                const uint32_t dk = desc_k0 + ka * (kSlotBytes >> 4);
#pragma unroll
                for (int ks = 0; ks < 8; ++ks)
                    wgmma_ss_n128(s, desc64(desc_q + (ks >> 2) * (8192 >> 4) + (ks & 3) * 2),
                                  desc64(dk + (ks >> 2) * (16384 >> 4) + (ks & 3) * 2), ks != 0);
            }
            wgmma_commit();
            if (j == 0) mbar_wait(bars + kBarQFull + 16 * wg + 8, t);
            mbar_wait(bars + kBarFull + 8 * kb, kb_ph);
            {
                const uint32_t dk = desc_k0 + kb * (kSlotBytes >> 4);
#pragma unroll
                for (int ks = 0; ks < 8; ++ks)
                    wgmma_ss_n128(s, desc64(desc_q + (2 + (ks >> 2)) * (8192 >> 4) + (ks & 3) * 2),
                                  desc64(dk + (ks >> 2) * (16384 >> 4) + (ks & 3) * 2), 1);
            }
            wgmma_commit();
            named_arrive(other_turn, 256);
            if (it == kItemsPerTile / 4) {
                asm volatile("fence.proxy.async.shared::cta;" ::: "memory");
                __syncwarp();
                if (lane == 0) mbar_arrive(bars + kBarStaged + 8 * wg);
            }
            wgmma_wait<1>();
            arrive_if(rel_ka, empty_remote + 8 * ka);
            wgmma_wait<0>();
            arrive_if(rel_kb, empty_remote + 8 * kb);
            arrive_local_if(sig_k, sig_k_bar);
            pin_regs(s);

            uint32_t p[32];
            float t0, t1;
            auto exp_steps = [&](int k0, int k1, float b0, float b1) {
#pragma unroll
                for (int i = 2 * k0; i < 2 * k1; ++i) {
                    const float e0 = ex2(fmaf(s[4 * i], kScaleLog2, -b0));
                    const float e1 = ex2(fmaf(s[4 * i + 1], kScaleLog2, -b0));
                    const float e2 = ex2(fmaf(s[4 * i + 2], kScaleLog2, -b1));
                    const float e3 = ex2(fmaf(s[4 * i + 3], kScaleLog2, -b1));
                    t0 += e0 + e1;
                    t1 += e2 + e3;
                    p[2 * i] = pack_bf16(e0, e1);
                    p[2 * i + 1] = pack_bf16(e2, e3);
                }
            };
            if (j == 0) {
                float x0 = fmaxf(fmaxf(s[0], s[1]), fmaxf(s[4], s[5]));
                float x1 = fmaxf(fmaxf(s[2], s[3]), fmaxf(s[6], s[7]));
                x0 = fmaxf(x0, __shfl_xor_sync(0xffffffffu, x0, 1));
                x1 = fmaxf(x1, __shfl_xor_sync(0xffffffffu, x1, 1));
                m0 = fmaxf(x0, __shfl_xor_sync(0xffffffffu, x0, 2));
                m1 = fmaxf(x1, __shfl_xor_sync(0xffffffffu, x1, 2));
            }
            t0 = t1 = 0.f;
            exp_steps(0, 4, m0 * kScaleLog2, m1 * kScaleLog2);
            const bool moved = upper_half_above(s, m0 + kLazyRaw, m1 + kLazyRaw) || !(t0 <= kLazySum) || !(t1 <= kLazySum);
            if (__any_sync(0xffffffffu, moved)) {
                float x0 = fmaxf(s[0], s[1]), x1 = fmaxf(s[2], s[3]);
                float y0 = fmaxf(s[4], s[5]), y1 = fmaxf(s[6], s[7]);
#pragma unroll
                for (int i = 2; i < 16; i += 2) {
                    x0 = fmaxf(x0, fmaxf(s[4 * i], s[4 * i + 1]));
                    x1 = fmaxf(x1, fmaxf(s[4 * i + 2], s[4 * i + 3]));
                    y0 = fmaxf(y0, fmaxf(s[4 * i + 4], s[4 * i + 5]));
                    y1 = fmaxf(y1, fmaxf(s[4 * i + 6], s[4 * i + 7]));
                }
                x0 = fmaxf(x0, y0);
                x1 = fmaxf(x1, y1);
                x0 = fmaxf(x0, __shfl_xor_sync(0xffffffffu, x0, 1));
                x1 = fmaxf(x1, __shfl_xor_sync(0xffffffffu, x1, 1));
                x0 = fmaxf(x0, __shfl_xor_sync(0xffffffffu, x0, 2));
                x1 = fmaxf(x1, __shfl_xor_sync(0xffffffffu, x1, 2));
                x0 = fmaxf(x0, m0);
                x1 = fmaxf(x1, m1);
                const float a0 = ex2((m0 - x0) * kScaleLog2), a1 = ex2((m1 - x1) * kScaleLog2);
                m0 = x0;
                m1 = x1;
                l0 *= a0;
                l1 *= a1;
                if (j != 0) {
#pragma unroll
                    for (int i = 0; i < 32; ++i) {
                        o[4 * i] *= a0;
                        o[4 * i + 1] *= a0;
                        o[4 * i + 2] *= a1;
                        o[4 * i + 3] *= a1;
                    }
                }
                t0 = t1 = 0.f;
                exp_steps(0, 4, m0 * kScaleLog2, m1 * kScaleLog2);
            }
            const float b0 = m0 * kScaleLog2, b1 = m1 * kScaleLog2;
            exp_steps(4, kStepsBeforePv, b0, b1);

            mbar_wait(bars + kBarFull + 8 * va, va_ph);
            named_sync(my_turn, 256);
            wgmma_rs_n256_x4(o, p, desc_v0 + va * (kSlotBytes >> 4), j != 0, never);
            exp_steps(kStepsBeforePv, 8, b0, b1);
            l0 += t0;
            l1 += t1;
            mbar_wait(bars + kBarFull + 8 * vb, vb_ph);
            wgmma_rs_n256_x4(o, p + 16, desc_v0 + vb * (kSlotBytes >> 4), 1, never);
            if (wg == 0 || it + 1 < kNumBlocks) named_arrive(other_turn, 256);
            if (j == 3) {
                l0 += __shfl_xor_sync(0xffffffffu, l0, 1);
                l1 += __shfl_xor_sync(0xffffffffu, l1, 1);
                l0 += __shfl_xor_sync(0xffffffffu, l0, 2);
                l1 += __shfl_xor_sync(0xffffffffu, l1, 2);
                inv0 = rcp(l0);
                inv1 = rcp(l1);
                if (it == 3) {
                    mbar_wait(bars + kBarStageOk + 8 * wg, 0);
                    mbar_wait(bars + kBarQFull + 16 * wg, 1);
                    mbar_wait(bars + kBarFull + 8 * slot_of(kItemsPerTile), phase_of(kItemsPerTile));
                }
            }

            const bool rel_va = wtid < 2 && item + 2 + kNumSlots < kNumItems;
            const bool rel_vb = wtid < 2 && item + 3 + kNumSlots < kNumItems && !(it == 3 && wg == 1);
            wgmma_wait<1>();
            arrive_if(rel_va, empty_remote + 8 * va);
            wgmma_wait<0>();
            arrive_if(rel_vb, empty_remote + 8 * vb);
            arrive_local_if(it == 3 && wg == 0 && wtid == 0, bars + kBarStageOk + 8);
            pin_regs(o);

            if (it == 3) {
                const int row = ((wtid >> 5) << 4) + (lane & 7) + (((lane >> 3) & 1) << 3);
                const uint32_t base = smem + kSmemRing + (wg == 0 ? kStageSlot0 : kStageSlot1) * kSlotBytes + row * 128 +
                                      ((((lane >> 4) ^ lane) & 7) << 4);
#pragma unroll
                for (int i = 0; i < 32; i += 2)
                    stage_blocks(o + 4 * i, inv0, inv1, (base ^ ((i & 7) << 4)) + (i >> 3) * 8192);
            }
        };
#pragma unroll 1
        for (int it = 0; it < kNumBlocks; ++it) key_block(it, block_config(it));

        {
            constexpr int kBlocks = 32 / kFinalParts;
            const uint32_t stage = smem + kSmemQ + wg * 32768 + (wtid >> 5) * 8192;
            const int row = (lane & 7) + (((lane >> 3) & 1) << 3);
            const uint32_t base = stage + row * 128 + ((((lane >> 4) ^ lane) & 7) << 4);
            const int out_row = ((kTilesPerCta - 1) * kNumCtas + tile0) * 128 + wg * 64 + (wtid >> 5) * 16;
#pragma unroll
            for (int h = 0; h < kFinalParts; ++h) {
#pragma unroll
                for (int i = kBlocks * h; i < kBlocks * h + kBlocks; i += 2)
                    stage_blocks(o + 4 * i, inv0, inv1, (base ^ ((i & 7) << 4)) + (i >> 3) * 2048);
                asm volatile("fence.proxy.async.shared::cta;" ::: "memory");
                __syncwarp();
                if (lane == 0) tma_store(&map_o16, stage + h * (8192 / kFinalParts), out_row, h * (4 / kFinalParts));
            }
            if (lane == 0) asm volatile("cp.async.bulk.wait_group.read 0;" ::: "memory");
        }
    }
}

typedef CUresult (*EncodeTiledFn)(CUtensorMap*, CUtensorMapDataType, cuuint32_t, void*, const cuuint64_t*,
                                  const cuuint64_t*, const cuuint32_t*, const cuuint32_t*, CUtensorMapInterleave,
                                  CUtensorMapSwizzle, CUtensorMapL2promotion, CUtensorMapFloatOOBfill);

void make_map(EncodeTiledFn enc, CUtensorMap* map, const void* ptr, uint32_t box_rows, uint32_t box_chunks) {
    const cuuint64_t dims[3] = {64, (cuuint64_t)kRows, 4};
    const cuuint64_t strides[2] = {512, 128};
    const cuuint32_t box[3] = {64, box_rows, box_chunks};
    const cuuint32_t estr[3] = {1, 1, 1};
    enc(map, CU_TENSOR_MAP_DATA_TYPE_BFLOAT16, 3, const_cast<void*>(ptr), dims, strides, box, estr,
        CU_TENSOR_MAP_INTERLEAVE_NONE, CU_TENSOR_MAP_SWIZZLE_128B, CU_TENSOR_MAP_L2_PROMOTION_L2_128B,
        CU_TENSOR_MAP_FLOAT_OOB_FILL_NONE);
}

}

extern "C" void kernel_launch(void* const* d_in, const int* in_sizes, int n_in, void* d_out, int out_size) {
    (void)in_sizes; (void)n_in; (void)out_size;
    static EncodeTiledFn enc = nullptr;
    if (!enc) {
        void* fn = nullptr;
        cudaDriverEntryPointQueryResult st;
        cudaGetDriverEntryPoint("cuTensorMapEncodeTiled", &fn, cudaEnableDefault, &st);
        enc = (EncodeTiledFn)fn;
        cudaFuncSetAttribute(gqa_fwd_kernel, cudaFuncAttributeMaxDynamicSharedMemorySize, kSmemBytes);
    }
    CUtensorMap mq, mk, mv, mo, mo16;
    make_map(enc, &mq, d_in[0], 64, 2);
    make_map(enc, &mk, d_in[1], 128, 1);
    make_map(enc, &mv, d_in[2], 64, 2);
    make_map(enc, &mo, d_out, 64, 4);
    make_map(enc, &mo16, d_out, 16, 4 / kFinalParts);
    gqa_fwd_kernel<<<kNumCtas, 384, kSmemBytes, cudaStreamPerThread>>>(
        mq, mk, mv, mo, mo16, (const uint8_t*)d_in[0], (const uint8_t*)d_in[1], (const uint8_t*)d_in[2]);
}
```
